```python
import torch

def _softmax(x, axis=-1):
    return torch.softmax(x, dim=axis)

def _gelu(x):
    return torch.nn.functional.gelu(x, approximate='tanh')

def _silu(x):
    return torch.nn.functional.silu(x)

def _sigmoid(x):
    return torch.sigmoid(x)

def _layernorm(x, axis=-1, eps=1e-05):
    m = x.mean(dim=axis, keepdim=True)
    v = x.var(dim=axis, keepdim=True, unbiased=False)
    return (x - m) / torch.sqrt(v + eps)

def _scatter_add(tgt, idx, src, axis=0):
    return tgt.clone().index_add_(axis, idx, src)

def _segment_sum(src, seg, n):
    out = torch.zeros((n,) + src.shape[1:], dtype=src.dtype)
    return out.index_add_(0, seg, src)

def _pad(x, pw):
    flat = tuple((v for pair in reversed(pw) for v in pair))
    return torch.nn.functional.pad(x, flat)
kernel_name = 'interleave_layers__linear_kernel_hedgehog__mixer_gmlp__prompt'

def setup_inputs():

    _w = lambda a: (lambda t: t.to(torch.bfloat16) if t.is_floating_point() else t)(torch.as_tensor(a))

    def _A_setup():
        B, S, D, H = (1, 2048, 640, 32)
        Dh = D // H
        return {'x': _w((lambda *s: torch.randn(*s, dtype=torch.bfloat16) * 0.05)(B, S, D)), 'wqkv': _w((lambda *s: torch.randn(*s, dtype=torch.bfloat16) * 0.4)(D, 3 * D)), 'w_phi': _w((lambda *s: torch.randn(*s, dtype=torch.bfloat16) * 0.4)(H, Dh, Dh) * Dh ** (-0.5)), 'wo': _w((lambda *s: torch.randn(*s, dtype=torch.bfloat16) * 0.05)(D, D))}
    _A_in = _A_setup()

    def _B_setup():
        B, S, D, F = (1, 2048, 640, 1536)
        Fh = F // 2
        return {'x': _w((lambda *s: torch.randn(*s, dtype=torch.bfloat16) * 0.05)(B, S, D)), 'w_in': _w((lambda *s: torch.randn(*s, dtype=torch.bfloat16) * 0.4)(D, 2 * Fh)), 'w_sp': _w(0.01 * (lambda *s: torch.randn(*s, dtype=torch.bfloat16) * 0.4)(S, S)), 'b_sp': _w(1.0 + 0.01 * (lambda *s: torch.randn(*s, dtype=torch.bfloat16) * 0.05)(S)), 'w_out': _w((lambda *s: torch.randn(*s, dtype=torch.bfloat16) * 0.05)(Fh, D))}
    _B_in = _B_setup()
    return {'A_x': _A_in['x'], 'A_wqkv': _A_in['wqkv'], 'A_w_phi': _A_in['w_phi'], 'A_wo': _A_in['wo'], 'B_x': _B_in['x'], 'B_w_in': _B_in['w_in'], 'B_w_sp': _B_in['w_sp'], 'B_b_sp': _B_in['b_sp'], 'B_w_out': _B_in['w_out']}

def reference(A_x, A_wqkv, A_w_phi, A_wo, B_x, B_w_in, B_w_sp, B_b_sp, B_w_out):

    def _A_ref(x, wqkv, w_phi, wo):
        B, S, D = x.shape
        H = 32
        Dh = D // H
        qkv = (lambda x, *d: x.permute(*d))((x @ wqkv).reshape(B, S, 3, H, Dh), 2, 0, 3, 1, 4)
        q, k, v = (qkv[0], qkv[1], qkv[2])
        pq = torch.einsum('bhsd,hdf->bhsf', q, w_phi)
        pk = torch.einsum('bhsd,hdf->bhsf', k, w_phi)
        phi_q = torch.concatenate([_softmax(pq, axis=-1), _softmax(-pq, axis=-1)], axis=-1)
        phi_k = torch.concatenate([_softmax(pk, axis=-1), _softmax(-pk, axis=-1)], axis=-1)
        kv = torch.einsum('bhsf,bhsd->bhfd', phi_k, v)
        z = torch.einsum('bhsf->bhf', phi_k)
        num = torch.einsum('bhqf,bhfd->bhqd', phi_q, kv)
        den = torch.einsum('bhqf,bhf->bhq', phi_q, z)[..., None] + 1e-06
        o = num / den
        return (lambda x, *d: x.permute(*d))(o, 0, 2, 1, 3).reshape(B, S, D) @ wo

    def _B_ref(x, w_in, w_sp, b_sp, w_out):
        B, S, D = x.shape
        F = w_in.shape[-1]
        Fh = F // 2
        z = _gelu(torch.einsum('bsd,df->bsf', x, w_in))
        z1 = z[..., :Fh].clone()
        z2 = _layernorm(z[..., Fh:], axis=-1)
        g = torch.einsum('ts,bsf->btf', w_sp, z2) + b_sp[None, :, None]
        return torch.einsum('bsf,fd->bsd', z1 * g, w_out)
    x = A_x
    x = x + _A_ref(_layernorm(x, axis=-1), A_wqkv, A_w_phi, A_wo)
    x = x + _B_ref(_layernorm(x, axis=-1), B_w_in, B_w_sp, B_b_sp, B_w_out)
    x = x + _A_ref(_layernorm(x, axis=-1), A_wqkv, A_w_phi, A_wo)
    x = x + _B_ref(_layernorm(x, axis=-1), B_w_in, B_w_sp, B_b_sp, B_w_out)
    return x
```

```cpp
#include <cuda_runtime.h>
#include <cuda_bf16.h>
#include <cuda.h>
#include <stdint.h>

namespace {

constexpr int S_ = 2048, D_ = 640, FH_ = 768;
constexpr int NCTA = 128;
constexpr int NTHREADS = 384;

constexpr int SA = 5, SB = 6;
constexpr int A_SLOT = 16384, B_SLOT = 12288;
constexpr int OFF_A = 0;
constexpr int OFF_B = OFF_A + SA * A_SLOT;
constexpr int OFF_STG = OFF_B + SB * B_SLOT;
constexpr int STG_WG = 33792;
constexpr int OFF_MISC = OFF_STG + 2 * STG_WG;
constexpr int OFF_BAR = OFF_MISC;
constexpr int OFF_ABORT = OFF_MISC + 240;
constexpr int OFF_CSQ = OFF_MISC + 256;
constexpr int OFF_CSI = OFF_CSQ + 240 * 4;
constexpr int OFF_STAT = OFF_MISC + 2048;
constexpr int SMEM_USED = OFF_STAT + 1024;
constexpr int SMEM_BYTES = SMEM_USED + 1024;
static_assert(OFF_STG % 1024 == 0 && STG_WG % 1024 == 0, "staging alignment");
static_assert(OFF_CSI + 192 * 4 <= OFF_STAT, "misc overlap");
static_assert(SMEM_BYTES <= 232448, "smem budget");
constexpr int PHK_HS = 5 * 1024 + 32;
constexpr int VS_OFF = 4 * PHK_HS;
constexpr int VS_HS = 3 * 1024 + 32;
constexpr int PHQ_HS = 6 * 1024 + 32;
constexpr int KVS_OFF = 4 * PHQ_HS;
static_assert(VS_OFF + 4 * VS_HS <= STG_WG && KVS_OFF + 7680 <= STG_WG && KVS_OFF % 128 == 0, "staging layout");

__device__ __nv_bfloat16 g_Wq[1920 * 640];
__device__ float g_csq_part[20 * 1920];
__device__ __nv_bfloat16 g_Wo[640 * 640];
__device__ __nv_bfloat16 g_Wi[1536 * 640];
__device__ float g_csi[1536];
__device__ __nv_bfloat16 g_Wout[640 * 768];
__device__ __nv_bfloat16 g_act[4 * S_ * D_];
__device__ __nv_bfloat16 g_h[S_ * FH_];
__device__ __nv_bfloat16 g_z[FH_ * S_];
__device__ float2 g_xstat[4 * 16 * 8 * 128];
__device__ float2 g_zstat[2 * 16 * 8 * 128];
__device__ float g_kv[2 * 8 * 3840];
constexpr int C_PRO = 0, C_BGA = 1, C_BGB = 2;
constexpr int C_KV = 3;
constexpr int C_Z2 = C_KV + 16;
constexpr int C_O = C_Z2 + 16;
constexpr int C_X1 = C_O + 64;
constexpr int C_ZS = C_X1 + 64;
constexpr int C_H = C_ZS + 64;
constexpr int C_X2 = C_H + 64;
constexpr int C_NUM = C_X2 + 32;
__device__ unsigned g_cnt[C_NUM * 32];
__device__ unsigned g_epoch;
#define PROF(i)
#define PROFW(i)

struct Maps {
  CUtensorMap x0, act, wsp, h, wq, wo, wi, z, wout;
  CUtensorMap sAct, sOut, sH, sZ;
};

__device__ __forceinline__ uint32_t smem_u32(const void* p) { return (uint32_t)__cvta_generic_to_shared(p); }
__device__ __forceinline__ uint32_t uniform(uint32_t x) {
  uint32_t y; asm volatile("mov.u32 %0, %1;" : "=r"(y) : "r"(x)); return __shfl_sync(0xffffffffu, y, 0);
}
__device__ __forceinline__ uint32_t opaque(uint32_t x) { uint32_t y; asm volatile("mov.u32 %0, %1;" : "=r"(y) : "r"(x)); return y; }
__device__ __forceinline__ bool elect_one() {
  uint32_t p; asm volatile("{ .reg .pred P; elect.sync _|P, 0xffffffff; selp.u32 %0, 1, 0, P; }" : "=r"(p)); return p;
}
__device__ __forceinline__ void mbar_init(uint32_t bar, uint32_t cnt) { asm volatile("mbarrier.init.shared::cta.b64 [%0], %1;" :: "r"(bar), "r"(cnt) : "memory"); }
__device__ __forceinline__ void mbar_expect_tx(uint32_t bar, uint32_t bytes) { asm volatile("mbarrier.arrive.expect_tx.shared::cta.b64 _, [%0], %1;" :: "r"(bar), "r"(bytes) : "memory"); }
__device__ __forceinline__ void mbar_arrive(uint32_t bar) { asm volatile("mbarrier.arrive.shared::cta.b64 _, [%0];" :: "r"(bar) : "memory"); }
__device__ __forceinline__ void mbar_wait(uint32_t bar, uint32_t parity, uint32_t abort_addr) {
  asm volatile("{\n .reg .pred p;\n .reg .u32 n, a;\n"
               " mbarrier.try_wait.parity.shared::cta.b64 p, [%0], %1;\n @p bra LAB_DONE;\n mov.u32 n, 0;\n"
               "LAB_WAIT:\n mbarrier.try_wait.parity.shared::cta.b64 p, [%0], %1;\n @p bra LAB_DONE;\n"
               " ld.volatile.shared.u32 a, [%2];\n setp.ne.u32 p, a, 0;\n @p bra LAB_DONE;\n"
               " add.u32 n, n, 1;\n setp.lt.u32 p, n, 1048576;\n @p bra LAB_WAIT;\n"
               " st.volatile.shared.u32 [%2], 1;\n LAB_DONE:\n }"
               :: "r"(bar), "r"(parity), "r"(abort_addr) : "memory");
}
__device__ __forceinline__ void tma_load(uint32_t dst, const CUtensorMap* map, int c0, int c1, uint32_t bar) {
  asm volatile("cp.async.bulk.tensor.2d.shared::cluster.global.mbarrier::complete_tx::bytes [%0], [%1, {%3, %4}], [%2];"
               :: "r"(dst), "l"(map), "r"(bar), "r"(c0), "r"(c1) : "memory");
}
__device__ __forceinline__ void tma_store2(const CUtensorMap* map, uint32_t src, int c0, int c1) {
  asm volatile("cp.async.bulk.tensor.2d.global.shared::cta.bulk_group [%0, {%2, %3}], [%1];" :: "l"(map), "r"(src), "r"(c0), "r"(c1) : "memory");
}
__device__ __forceinline__ void tma_store3(const CUtensorMap* map, uint32_t src, int c0, int c1, int c2) {
  asm volatile("cp.async.bulk.tensor.3d.global.shared::cta.bulk_group [%0, {%2, %3, %4}], [%1];" :: "l"(map), "r"(src), "r"(c0), "r"(c1), "r"(c2) : "memory");
}
__device__ __forceinline__ void bulk_store(void* dst, uint32_t src, uint32_t bytes) {
  asm volatile("cp.async.bulk.global.shared::cta.bulk_group [%0], [%1], %2;" :: "l"(dst), "r"(src), "r"(bytes) : "memory");
}
__device__ __forceinline__ void bulk_reduce_add_f32(void* dst, uint32_t src, uint32_t bytes) {
  asm volatile("cp.reduce.async.bulk.global.shared::cta.bulk_group.add.f32 [%0], [%1], %2;" :: "l"(dst), "r"(src), "r"(bytes) : "memory");
}
__device__ __forceinline__ void bulk_commit_wait() {
  asm volatile("cp.async.bulk.commit_group;" ::: "memory");
  asm volatile("cp.async.bulk.wait_group 0;" ::: "memory");
}
__device__ __forceinline__ void fence_async_smem() { asm volatile("fence.proxy.async.shared::cta;" ::: "memory"); }
__device__ __forceinline__ void fence_async_global() { asm volatile("fence.proxy.async.global;" ::: "memory"); }
__device__ __forceinline__ void bar_sync(int id, int n) { asm volatile("bar.sync %0, %1;" :: "r"(id), "r"(n) : "memory"); }
__device__ __forceinline__ void cnt_add(int idx) { asm volatile("red.relaxed.gpu.global.add.u32 [%0], 1;" :: "l"(&g_cnt[idx * 32]) : "memory"); }
__device__ __forceinline__ void cnt_wait(int idx, unsigned target, uint32_t abort_addr) {
  asm volatile("{\n .reg .pred p;\n .reg .u32 n, v, a;\n mov.u32 n, 0;\n"
               "LAB_WAIT:\n ld.relaxed.gpu.global.u32 v, [%0];\n sub.u32 v, v, %1;\n setp.ge.s32 p, v, 0;\n @p bra LAB_DONE;\n"
               " ld.volatile.shared.u32 a, [%2];\n setp.ne.u32 p, a, 0;\n @p bra LAB_DONE;\n"
               " add.u32 n, n, 1;\n setp.lt.u32 p, n, 1048576;\n @p bra LAB_WAIT;\n"
               " st.volatile.shared.u32 [%2], 1;\n LAB_DONE:\n }"
               :: "l"(&g_cnt[idx * 32]), "r"(target), "r"(abort_addr) : "memory");
}
__device__ __forceinline__ void cnt_wait_warp(int idx, unsigned target, uint32_t abort_addr) {
  if ((threadIdx.x & 31) == 0) cnt_wait(idx, target, abort_addr);
  __syncwarp();
}
__device__ __forceinline__ uint64_t make_desc(uint32_t saddr, uint32_t lbo, uint32_t sbo, uint64_t layout) {
  return (uint64_t)((saddr & 0x3FFFF) >> 4) | ((uint64_t)(lbo >> 4) << 16) | ((uint64_t)(sbo >> 4) << 32) | (layout << 62);
}
__device__ __forceinline__ void wg_fence() { asm volatile("wgmma.fence.sync.aligned;" ::: "memory"); }
__device__ __forceinline__ void wg_commit() { asm volatile("wgmma.commit_group.sync.aligned;" ::: "memory"); }
template <int N> __device__ __forceinline__ void wg_wait() { asm volatile("wgmma.wait_group.sync.aligned %0;" :: "n"(N) : "memory"); }
template <int N> __device__ __forceinline__ void fresh(float (&a)[N]) {
#pragma unroll
  for (int i = 0; i < N; i++) asm volatile("mov.b32 %0, 0;" : "=f"(a[i]));
}
template <int N> __device__ __forceinline__ void pin(float (&a)[N]) {
#pragma unroll
  for (int i = 0; i < N; i++) asm volatile("" : "+f"(a[i]) :: "memory");
}
__device__ __forceinline__ uint32_t pack2(float lo, float hi) {
  uint32_t r; asm("cvt.rn.bf16x2.f32 %0, %1, %2;" : "=r"(r) : "f"(hi), "f"(lo)); return r;
}
__device__ __forceinline__ float bf_lo(uint32_t v) { return __uint_as_float(v << 16); }
__device__ __forceinline__ float bf_hi(uint32_t v) { return __uint_as_float(v & 0xffff0000u); }
__device__ __forceinline__ float ex2(float x) { float y; asm("ex2.approx.ftz.f32 %0, %1;" : "=f"(y) : "f"(x)); return y; }
__device__ __forceinline__ float rcp(float x) { float y; asm("rcp.approx.ftz.f32 %0, %1;" : "=f"(y) : "f"(x)); return y; }
__device__ __forceinline__ float gelu(float x) {
  float u = x * fmaf(x * x, 0.0356774081363f, 0.7978845608029f), t;
  asm("tanh.approx.f32 %0, %1;" : "=f"(t) : "f"(u));
  float hx = 0.5f * x;
  return fmaf(hx, t, hx);
}
__device__ __forceinline__ void sts128(uint32_t a, uint32_t x, uint32_t y, uint32_t z, uint32_t w) {
  asm volatile("st.shared.v4.u32 [%0], {%1, %2, %3, %4};" :: "r"(a), "r"(x), "r"(y), "r"(z), "r"(w) : "memory");
}
__device__ __forceinline__ void sts32(uint32_t a, uint32_t x) { asm volatile("st.shared.u32 [%0], %1;" :: "r"(a), "r"(x) : "memory"); }
__device__ __forceinline__ void sts64f(uint32_t a, float x, float y) { asm volatile("st.shared.v2.f32 [%0], {%1, %2};" :: "r"(a), "f"(x), "f"(y) : "memory"); }
__device__ __forceinline__ float2 lds64f(uint32_t a) { float2 v; asm volatile("ld.shared.v2.f32 {%0, %1}, [%2];" : "=f"(v.x), "=f"(v.y) : "r"(a)); return v; }
__device__ __forceinline__ void stsm4(uint32_t a, uint32_t r0, uint32_t r1, uint32_t r2, uint32_t r3) {
  asm volatile("stmatrix.sync.aligned.m8n8.x4.shared.b16 [%0], {%1, %2, %3, %4};" :: "r"(a), "r"(r0), "r"(r1), "r"(r2), "r"(r3) : "memory");
}
__device__ __forceinline__ void stsm4t(uint32_t a, uint32_t r0, uint32_t r1, uint32_t r2, uint32_t r3) {
  asm volatile("stmatrix.sync.aligned.m8n8.x4.trans.shared.b16 [%0], {%1, %2, %3, %4};" :: "r"(a), "r"(r0), "r"(r1), "r"(r2), "r"(r3) : "memory");
}
__device__ __forceinline__ void mma16816(float (&c)[4], const uint32_t (&a)[4], uint32_t b0, uint32_t b1) {
  asm volatile("mma.sync.aligned.m16n8k16.row.col.f32.bf16.bf16.f32 {%0, %1, %2, %3}, {%4, %5, %6, %7}, {%8, %9}, {%0, %1, %2, %3};"
               : "+f"(c[0]), "+f"(c[1]), "+f"(c[2]), "+f"(c[3]) : "r"(a[0]), "r"(a[1]), "r"(a[2]), "r"(a[3]), "r"(b0), "r"(b1));
}

template <int TA, int TB>
__device__ __forceinline__ void wgmma_n24(float (&d)[12], uint64_t da, uint64_t db, int scale_d) {
  asm volatile("{ .reg .pred p; setp.ne.b32 p, %14, 0; "
    "wgmma.mma_async.sync.aligned.m64n24k16.f32.bf16.bf16 "
    "{%0, %1, %2, %3, %4, %5, %6, %7, %8, %9, %10, %11}, "
    "%12, %13, p, 1, 1, %15, %16; }"
    : "+f"(d[0]), "+f"(d[1]), "+f"(d[2]), "+f"(d[3]), "+f"(d[4]), "+f"(d[5]), "+f"(d[6]), "+f"(d[7]), "+f"(d[8]), "+f"(d[9]), "+f"(d[10]), "+f"(d[11])
    : "l"(da), "l"(db), "r"(scale_d), "n"(TA), "n"(TB));
}
template <int TA, int TB>
__device__ __forceinline__ void wgmma_n80(float (&d)[40], uint64_t da, uint64_t db, int scale_d) {
  asm volatile("{ .reg .pred p; setp.ne.b32 p, %42, 0; "
    "wgmma.mma_async.sync.aligned.m64n80k16.f32.bf16.bf16 "
    "{%0, %1, %2, %3, %4, %5, %6, %7, %8, %9, %10, %11, %12, %13, %14, %15, %16, %17, %18, %19, %20, %21, %22, %23, %24, %25, %26, %27, %28, %29, %30, %31, %32, %33, %34, %35, %36, %37, %38, %39}, "
    "%40, %41, p, 1, 1, %43, %44; }"
    : "+f"(d[0]), "+f"(d[1]), "+f"(d[2]), "+f"(d[3]), "+f"(d[4]), "+f"(d[5]), "+f"(d[6]), "+f"(d[7]), "+f"(d[8]), "+f"(d[9]), "+f"(d[10]), "+f"(d[11]), "+f"(d[12]), "+f"(d[13]), "+f"(d[14]), "+f"(d[15]), "+f"(d[16]), "+f"(d[17]), "+f"(d[18]), "+f"(d[19]), "+f"(d[20]), "+f"(d[21]), "+f"(d[22]), "+f"(d[23]), "+f"(d[24]), "+f"(d[25]), "+f"(d[26]), "+f"(d[27]), "+f"(d[28]), "+f"(d[29]), "+f"(d[30]), "+f"(d[31]), "+f"(d[32]), "+f"(d[33]), "+f"(d[34]), "+f"(d[35]), "+f"(d[36]), "+f"(d[37]), "+f"(d[38]), "+f"(d[39])
    : "l"(da), "l"(db), "r"(scale_d), "n"(TA), "n"(TB));
}
template <int TA, int TB>
__device__ __forceinline__ void wgmma_n96(float (&d)[48], uint64_t da, uint64_t db, int scale_d) {
  asm volatile("{ .reg .pred p; setp.ne.b32 p, %50, 0; "
    "wgmma.mma_async.sync.aligned.m64n96k16.f32.bf16.bf16 "
    "{%0, %1, %2, %3, %4, %5, %6, %7, %8, %9, %10, %11, %12, %13, %14, %15, %16, %17, %18, %19, %20, %21, %22, %23, %24, %25, %26, %27, %28, %29, %30, %31, %32, %33, %34, %35, %36, %37, %38, %39, %40, %41, %42, %43, %44, %45, %46, %47}, "
    "%48, %49, p, 1, 1, %51, %52; }"
    : "+f"(d[0]), "+f"(d[1]), "+f"(d[2]), "+f"(d[3]), "+f"(d[4]), "+f"(d[5]), "+f"(d[6]), "+f"(d[7]), "+f"(d[8]), "+f"(d[9]), "+f"(d[10]), "+f"(d[11]), "+f"(d[12]), "+f"(d[13]), "+f"(d[14]), "+f"(d[15]), "+f"(d[16]), "+f"(d[17]), "+f"(d[18]), "+f"(d[19]), "+f"(d[20]), "+f"(d[21]), "+f"(d[22]), "+f"(d[23]), "+f"(d[24]), "+f"(d[25]), "+f"(d[26]), "+f"(d[27]), "+f"(d[28]), "+f"(d[29]), "+f"(d[30]), "+f"(d[31]), "+f"(d[32]), "+f"(d[33]), "+f"(d[34]), "+f"(d[35]), "+f"(d[36]), "+f"(d[37]), "+f"(d[38]), "+f"(d[39]), "+f"(d[40]), "+f"(d[41]), "+f"(d[42]), "+f"(d[43]), "+f"(d[44]), "+f"(d[45]), "+f"(d[46]), "+f"(d[47])
    : "l"(da), "l"(db), "r"(scale_d), "n"(TA), "n"(TB));
}

template <int N, int TA, int TB>
__device__ __forceinline__ void wgmma(float (&d)[N / 2], uint64_t da, uint64_t db, int s) {
  if constexpr (N == 24) wgmma_n24<TA, TB>(d, da, db, s);
  else if constexpr (N == 80) wgmma_n80<TA, TB>(d, da, db, s);
  else wgmma_n96<TA, TB>(d, da, db, s);
}

struct Pipe {
  uint32_t fullA, emptyA, fullB, emptyB, ab;
  uint64_t dA, dB;
  int sa, sb;
  uint32_t pa, pb;
  bool leader;
  __device__ __forceinline__ void advA() { if (++sa == SA) { sa = 0; pa ^= 1; } }
  __device__ __forceinline__ void advB() { if (++sb == SB) { sb = 0; pb ^= 1; } }
};

template <int N, int NK>
__device__ __forceinline__ void gemm1(float (&acc)[N / 2], Pipe& p) {
  int ra = 0, rb = 0;
  fresh(acc);
#pragma unroll 1
  for (int kb = 0; kb < NK; kb++) {
    mbar_wait(p.fullB + p.sb * 8, p.pb, p.ab);
    mbar_wait(p.fullA + p.sa * 8, p.pa, p.ab);
    wg_fence();
    const uint64_t da = p.dA + (uint64_t)(p.sa * (A_SLOT >> 4)), db = p.dB + (uint64_t)(p.sb * (B_SLOT >> 4));
#pragma unroll
    for (int k = 0; k < 4; k++) wgmma<N, 0, 0>(acc, da + k * 2, db + k * 2, (kb > 0 || k > 0) ? 1 : 0);
    wg_commit();
    wg_wait<1>();
    if (kb > 0 && p.leader) { mbar_arrive(p.emptyA + ra * 8); mbar_arrive(p.emptyB + rb * 8); }
    ra = p.sa; rb = p.sb;
    p.advA(); p.advB();
  }
  wg_wait<0>();
  pin(acc);
  if (p.leader) { mbar_arrive(p.emptyA + ra * 8); mbar_arrive(p.emptyB + rb * 8); }
}
template <int N, int NK>
__device__ __forceinline__ void gemm2(float (&acc0)[N / 2], float (&acc1)[N / 2], Pipe& p) {
  int ra = 0, rb0 = 0, rb1 = 0;
  fresh(acc0); fresh(acc1);
#pragma unroll 1
  for (int kb = 0; kb < NK; kb++) {
    const int s0 = p.sb; const uint32_t p0 = p.pb;
    p.advB();
    const int s1 = p.sb; const uint32_t p1 = p.pb;
    p.advB();
    mbar_wait(p.fullB + s0 * 8, p0, p.ab);
    mbar_wait(p.fullB + s1 * 8, p1, p.ab);
    mbar_wait(p.fullA + p.sa * 8, p.pa, p.ab);
    wg_fence();
    const uint64_t da = p.dA + (uint64_t)(p.sa * (A_SLOT >> 4));
    const uint64_t db0 = p.dB + (uint64_t)(s0 * (B_SLOT >> 4)), db1 = p.dB + (uint64_t)(s1 * (B_SLOT >> 4));
#pragma unroll
    for (int k = 0; k < 4; k++) {
      wgmma<N, 0, 0>(acc0, da + k * 2, db0 + k * 2, (kb > 0 || k > 0) ? 1 : 0);
      wgmma<N, 0, 0>(acc1, da + k * 2, db1 + k * 2, (kb > 0 || k > 0) ? 1 : 0);
    }
    wg_commit();
    wg_wait<1>();
    if (kb > 0 && p.leader) { mbar_arrive(p.emptyA + ra * 8); mbar_arrive(p.emptyB + rb0 * 8); mbar_arrive(p.emptyB + rb1 * 8); }
    ra = p.sa; rb0 = s0; rb1 = s1;
    p.advA();
  }
  wg_wait<0>();
  pin(acc0); pin(acc1);
  if (p.leader) { mbar_arrive(p.emptyA + ra * 8); mbar_arrive(p.emptyB + rb0 * 8); mbar_arrive(p.emptyB + rb1 * 8); }
}

__device__ __forceinline__ void row_stats(const float2* part, int rl, int q, float inv_n, float& m0, float& r0, float& m1, float& r1) {
  const float2 a0 = __ldcg(part + (2 * q) * 128 + rl), a1 = __ldcg(part + (2 * q + 1) * 128 + rl);
  const float2 b0 = __ldcg(part + (2 * q) * 128 + rl + 8), b1 = __ldcg(part + (2 * q + 1) * 128 + rl + 8);
  float s0 = a0.x + a1.x, t0 = a0.y + a1.y, s1 = b0.x + b1.x, t1 = b0.y + b1.y;
#pragma unroll
  for (int o = 1; o <= 2; o <<= 1) {
    s0 += __shfl_xor_sync(0xffffffffu, s0, o); t0 += __shfl_xor_sync(0xffffffffu, t0, o);
    s1 += __shfl_xor_sync(0xffffffffu, s1, o); t1 += __shfl_xor_sync(0xffffffffu, t1, o);
  }
  m0 = s0 * inv_n; m1 = s1 * inv_n;
  r0 = rsqrtf(fmaxf(t0 * inv_n - m0 * m0, 0.f) + 1e-5f);
  r1 = rsqrtf(fmaxf(t1 * inv_n - m1 * m1, 0.f) + 1e-5f);
}

__device__ __forceinline__ void feature_map_store(const float (&t)[20], uint32_t addr) {
  float mx = t[0], mn = t[0];
#pragma unroll
  for (int f = 1; f < 20; f++) { mx = fmaxf(mx, t[f]); mn = fminf(mn, t[f]); }
  float ep[20], en[20], sp = 0.f, sn = 0.f;
#pragma unroll
  for (int f = 0; f < 20; f++) { ep[f] = ex2(t[f] - mx); sp += ep[f]; en[f] = ex2(mn - t[f]); sn += en[f]; }
  const float rp = rcp(sp), rn = rcp(sn);
  uint32_t w[20];
#pragma unroll
  for (int f = 0; f < 10; f++) { w[f] = pack2(ep[2 * f] * rp, ep[2 * f + 1] * rp); w[10 + f] = pack2(en[2 * f] * rn, en[2 * f + 1] * rn); }
#pragma unroll
  for (int c = 0; c < 5; c++) sts128(addr + c * 1024, w[4 * c], w[4 * c + 1], w[4 * c + 2], w[4 * c + 3]);
}

__device__ __forceinline__ void feature_rows(const float (&acc)[40], uint32_t cs_addr, int q, float a0, float m0, float a1, float m1, uint32_t addr) {
#pragma unroll
  for (int h = 0; h < 2; h++) {
    const float a = h ? a1 : a0, bm = h ? -m1 * a1 : -m0 * a0;
    float t[20];
#pragma unroll
    for (int i = 0; i < 10; i++) {
      const float2 c = lds64f(cs_addr + (8 * i + 2 * q) * 4);
      t[2 * i] = fmaf(acc[4 * i + 2 * h], a, bm * c.x);
      t[2 * i + 1] = fmaf(acc[4 * i + 2 * h + 1], a, bm * c.y);
    }
    feature_map_store(t, addr + h * 128);
  }
}

__device__ __forceinline__ void resid_epilogue(const float (&acc)[40], const uint32_t (&res)[20], uint32_t stg, uint32_t statS, int wg, int w4, int lane,
                                               const CUtensorMap* map, int col, int row_tma, float2* stat_dst, int cnt_idx) {
  const int g = lane >> 2, q = lane & 3;
  uint32_t o[20];
  float s0 = 0.f, t0 = 0.f, s1 = 0.f, t1 = 0.f;
#pragma unroll
  for (int i = 0; i < 10; i++) {
    o[2 * i] = pack2(acc[4 * i] + bf_lo(res[2 * i]), acc[4 * i + 1] + bf_hi(res[2 * i]));
    o[2 * i + 1] = pack2(acc[4 * i + 2] + bf_lo(res[2 * i + 1]), acc[4 * i + 3] + bf_hi(res[2 * i + 1]));
    float a = bf_lo(o[2 * i]), b = bf_hi(o[2 * i]), c = bf_lo(o[2 * i + 1]), d = bf_hi(o[2 * i + 1]);
    s0 += a + b; t0 = fmaf(a, a, fmaf(b, b, t0)); s1 += c + d; t1 = fmaf(c, c, fmaf(d, d, t1));
  }
  bar_sync(1 + wg, 128);
  const uint32_t rowaddr = stg + (16 * w4 + (lane & 15)) * 160 + (lane >> 4) * 16;
#pragma unroll
  for (int i = 0; i < 10; i += 2) stsm4(rowaddr + i * 16, o[2 * i], o[2 * i + 1], o[2 * i + 2], o[2 * i + 3]);
  if (stat_dst != nullptr) {
#pragma unroll
    for (int m = 1; m <= 2; m <<= 1) {
      s0 += __shfl_xor_sync(0xffffffffu, s0, m); t0 += __shfl_xor_sync(0xffffffffu, t0, m);
      s1 += __shfl_xor_sync(0xffffffffu, s1, m); t1 += __shfl_xor_sync(0xffffffffu, t1, m);
    }
    if (q == 0) { sts64f(statS + (16 * w4 + g) * 8, s0, t0); sts64f(statS + (16 * w4 + g + 8) * 8, s1, t1); }
  }
  fence_async_smem();
  bar_sync(1 + wg, 128);
  if (w4 == 0) {
    if (elect_one()) {
      tma_store2(map, stg, col, row_tma);
      if (stat_dst != nullptr) bulk_store(stat_dst, statS, 512);
      bulk_commit_wait();
      if (cnt_idx >= 0) cnt_add(cnt_idx);
    }
    __syncwarp();
  }
}

__device__ __forceinline__ void load_resid(uint32_t (&res)[20], const __nv_bfloat16* x, int row0, int col0, int q) {
  const uint32_t* p0 = reinterpret_cast<const uint32_t*>(x + (size_t)row0 * D_ + col0 + 2 * q);
  const uint32_t* p1 = reinterpret_cast<const uint32_t*>(x + (size_t)(row0 + 8) * D_ + col0 + 2 * q);
#pragma unroll
  for (int i = 0; i < 10; i++) { res[2 * i] = __ldcg(p0 + 4 * i); res[2 * i + 1] = __ldcg(p1 + 4 * i); }
}

struct Params {
  const __nv_bfloat16 *x, *wqkv, *wphi, *wo, *win, *wsp, *bsp, *wout;
};

__device__ __forceinline__ void transpose_strip(const __nv_bfloat16* src, int ldn, int K, int n0, __nv_bfloat16* dst, int drow, float* colsum, int lane) {
  float cs[8];
#pragma unroll
  for (int c = 0; c < 8; c++) cs[c] = 0.f;
  const bool odd = lane & 1;
  for (int k0 = 0; k0 < K; k0 += 128) {
    uint4 v[4];
#pragma unroll
    for (int u = 0; u < 4; u++) v[u] = __ldg(reinterpret_cast<const uint4*>(src + (size_t)(k0 + 32 * u + lane) * ldn + n0));
#pragma unroll
    for (int u = 0; u < 4; u++) {
      if (colsum != nullptr) {
        cs[0] += bf_lo(v[u].x); cs[1] += bf_hi(v[u].x); cs[2] += bf_lo(v[u].y); cs[3] += bf_hi(v[u].y);
        cs[4] += bf_lo(v[u].z); cs[5] += bf_hi(v[u].z); cs[6] += bf_lo(v[u].w); cs[7] += bf_hi(v[u].w);
      }
      const uint32_t r0 = __shfl_xor_sync(0xffffffffu, odd ? v[u].x : v[u].z, 1);
      const uint32_t r1 = __shfl_xor_sync(0xffffffffu, odd ? v[u].y : v[u].w, 1);
      const uint32_t lo0 = odd ? r0 : v[u].x, hi0 = odd ? v[u].z : r0;
      const uint32_t lo1 = odd ? r1 : v[u].y, hi1 = odd ? v[u].w : r1;
      __nv_bfloat16* d = dst + (size_t)(drow + (odd ? 4 : 0)) * K + k0 + 32 * u + (lane & ~1);
      *reinterpret_cast<uint32_t*>(d) = __byte_perm(lo0, hi0, 0x5410);
      *reinterpret_cast<uint32_t*>(d + K) = __byte_perm(lo0, hi0, 0x7632);
      *reinterpret_cast<uint32_t*>(d + 2 * K) = __byte_perm(lo1, hi1, 0x5410);
      *reinterpret_cast<uint32_t*>(d + 3 * K) = __byte_perm(lo1, hi1, 0x7632);
    }
  }
  if (colsum != nullptr) {
#pragma unroll
    for (int c = 0; c < 8; c++) {
#pragma unroll
      for (int m = 16; m >= 1; m >>= 1) cs[c] += __shfl_xor_sync(0xffffffffu, cs[c], m);
    }
    if (lane == 0) {
#pragma unroll
      for (int c = 0; c < 8; c++) colsum[drow + c] = cs[c];
    }
  }
}

__device__ __forceinline__ void prologue(const Params& P, int b, int r, int j, uint32_t stg_base, int warp, int lane) {
  const int g = lane >> 2, q = lane & 3, t256 = threadIdx.x;
  uint4 xv[5];
  {
    const uint4* px = reinterpret_cast<const uint4*>(P.x + (size_t)(128 * r + (t256 >> 1)) * D_ + 80 * j + 40 * (t256 & 1));
#pragma unroll
    for (int i = 0; i < 5; i++) xv[i] = __ldg(px + i);
  }
  if (b < 120) {
    const int kr = b % 20, cg = b / 20, t = cg >> 1, hb = 16 * (cg & 1);
    uint32_t bf[2][4][3];
#pragma unroll
    for (int hh = 0; hh < 2; hh++) {
      const int h = hb + 2 * warp + hh;
#pragma unroll
      for (int nt = 0; nt < 4; nt++) {
        const uint32_t* pw = reinterpret_cast<const uint32_t*>(P.wqkv + (size_t)(32 * kr + 8 * nt + g) * 1920 + 640 * t + 20 * h + 2 * q);
        bf[hh][nt][0] = __ldg(pw);
        bf[hh][nt][1] = __ldg(pw + 4);
        bf[hh][nt][2] = q < 2 ? __ldg(pw + 8) : 0u;
      }
    }
    const uint32_t wp = stg_base + warp * 1600;
    if (t < 2) {
      const uint4* src = reinterpret_cast<const uint4*>(P.wphi + (size_t)(hb + 2 * warp) * 400);
#pragma unroll
      for (int i = 0; i < 4; i++) {
        const int c = lane + 32 * i;
        if (c < 100) { const uint4 v = __ldg(src + c); sts128(wp + c * 16, v.x, v.y, v.z, v.w); }
      }
      __syncwarp();
    }
    const int part = t == 1 ? 0 : (t == 2 ? 1 : 2);
#pragma unroll
    for (int hh = 0; hh < 2; hh++) {
      const int h = hb + 2 * warp + hh;
      auto aval = [&](int f, int d) -> uint32_t {
        if (f >= 20 || d >= 20) return 0u;
        if (t == 2) return f == d ? 0x3f80u : 0u;
        uint16_t v; asm volatile("ld.shared.u16 %0, [%1];" : "=h"(v) : "r"(wp + hh * 800 + (d * 20 + f) * 2)); return v;
      };
#pragma unroll
      for (int mt = 0; mt < 2; mt++) {
        uint32_t a0[4], a1[4];
        const int f0 = 16 * mt + g, f1 = f0 + 8, d0 = 2 * q;
        a0[0] = aval(f0, d0) | (aval(f0, d0 + 1) << 16); a0[1] = aval(f1, d0) | (aval(f1, d0 + 1) << 16);
        a0[2] = aval(f0, d0 + 8) | (aval(f0, d0 + 9) << 16); a0[3] = aval(f1, d0 + 8) | (aval(f1, d0 + 9) << 16);
        a1[0] = aval(f0, d0 + 16) | (aval(f0, d0 + 17) << 16); a1[1] = aval(f1, d0 + 16) | (aval(f1, d0 + 17) << 16);
        a1[2] = 0u; a1[3] = 0u;
        float cs0 = 0.f, cs1 = 0.f;
        const int n0 = 240 * (h >> 2) + 80 * part + 8 * (f0 >> 1) + 2 * (h & 3) + (f0 & 1);
        const int n1 = n0 + 32;
#pragma unroll
        for (int nt = 0; nt < 4; nt++) {
          float c[4] = {0.f, 0.f, 0.f, 0.f};
          mma16816(c, a0, bf[hh][nt][0], bf[hh][nt][1]);
          mma16816(c, a1, bf[hh][nt][2], 0u);
          const uint32_t lo = pack2(c[0], c[1]), hi = pack2(c[2], c[3]);
          cs0 += bf_lo(lo) + bf_hi(lo); cs1 += bf_lo(hi) + bf_hi(hi);
          if (f0 < 20) *reinterpret_cast<uint32_t*>(g_Wq + (size_t)n0 * 640 + 32 * kr + 8 * nt + 2 * q) = lo;
          if (f1 < 20) *reinterpret_cast<uint32_t*>(g_Wq + (size_t)n1 * 640 + 32 * kr + 8 * nt + 2 * q) = hi;
        }
        cs0 += __shfl_xor_sync(0xffffffffu, cs0, 1); cs0 += __shfl_xor_sync(0xffffffffu, cs0, 2);
        cs1 += __shfl_xor_sync(0xffffffffu, cs1, 1); cs1 += __shfl_xor_sync(0xffffffffu, cs1, 2);
        if (q == 0) {
          if (f0 < 20) g_csq_part[kr * 1920 + n0] = cs0;
          if (f1 < 20) g_csq_part[kr * 1920 + n1] = cs1;
        }
      }
    }
  }
  {
    float s = 0.f, t = 0.f;
#pragma unroll
    for (int i = 0; i < 5; i++) {
      const uint32_t w[4] = {xv[i].x, xv[i].y, xv[i].z, xv[i].w};
#pragma unroll
      for (int c = 0; c < 4; c++) { const float a = bf_lo(w[c]), bb = bf_hi(w[c]); s += a + bb; t = fmaf(a, a, fmaf(bb, bb, t)); }
    }
    s += __shfl_xor_sync(0xffffffffu, s, 1); t += __shfl_xor_sync(0xffffffffu, t, 1);
    if ((t256 & 1) == 0) g_xstat[(0 * 16 + r) * 1024 + j * 128 + (t256 >> 1)] = make_float2(s, t);
  }
  if (t256 < 120) reinterpret_cast<float4*>(g_kv)[b * 120 + t256] = make_float4(0.f, 0.f, 0.f, 0.f);
}

__global__ void __launch_bounds__(NTHREADS, 1) mega_kernel(const __grid_constant__ Maps M, const Params P, __nv_bfloat16* __restrict__ out) {
  extern __shared__ uint8_t smem_raw[];
  const uint32_t sb = uniform((smem_u32(smem_raw) + 1023) & ~1023u);
  const int warp = uniform(threadIdx.x >> 5), lane = threadIdx.x & 31;
  const int b = uniform(blockIdx.x), r = b >> 3, j = b & 7;
  const uint32_t fullA = sb + OFF_BAR, emptyA = fullA + SA * 8, fullB = emptyA + SA * 8, emptyB = fullB + SB * 8;
  const uint32_t ab = sb + OFF_ABORT;
  PROF(0);
  if (threadIdx.x == 0) {
    asm volatile("st.shared.u32 [%0], 0;" :: "r"(ab) : "memory");
    for (int s = 0; s < SA; s++) { mbar_init(fullA + s * 8, 1); mbar_init(emptyA + s * 8, 2); }
    for (int s = 0; s < SB; s++) { mbar_init(fullB + s * 8, 1); mbar_init(emptyB + s * 8, 2); }
    asm volatile("fence.mbarrier_init.release.cluster;" ::: "memory");
  }
  const unsigned ep1 = uniform(*(volatile unsigned*)&g_epoch) + 1;
  __syncthreads();

  if (warp >= 8) {
    asm volatile("setmaxnreg.dec.sync.aligned.u32 56;");
    if (warp == 8) {
      int s = 0; uint32_t ph = 1;
      auto load = [&](const CUtensorMap* map, int nk, int row) {
#pragma unroll 1
        for (int kb = 0; kb < nk; kb++) {
          mbar_wait(emptyA + s * 8, ph, ab);
          if (elect_one()) { mbar_expect_tx(fullA + s * 8, A_SLOT); tma_load(sb + OFF_A + s * A_SLOT, map, kb * 64, row, fullA + s * 8); }
          __syncwarp();
          if (++s == SA) { s = 0; ph ^= 1; }
        }
      };
      auto dep = [&](int c) {
        if (lane < 2) cnt_wait(c + lane, ep1 * 8, ab);
        __syncwarp();
        fence_async_global();
      };
#pragma unroll 1
      for (int l = 0; l < 2; l++) {
        const CUtensorMap* mx = l == 0 ? &M.x0 : &M.act;
        const int rx = l == 0 ? 128 * r : 2 * S_ + 128 * r;
        if (l == 1) dep(C_X2 + 2 * r);
        load(mx, 10, rx);
        load(mx, 10, rx);
        dep(C_O + l * 32 + 2 * r);
        load(&M.act, 10, 128 * r);
        dep(C_X1 + l * 32 + 2 * r);
        const int r1 = (l == 0 ? 1 : 3) * S_ + 128 * r;
        load(&M.act, 10, r1);
        load(&M.act, 10, r1);
        load(&M.wsp, 32, 128 * r);
        dep(C_H + l * 32 + 2 * r);
        load(&M.h, 12, 128 * r);
      }
    } else if (warp == 9) {
      int s = 0; uint32_t ph = 1;
      auto load1 = [&](const CUtensorMap* map, int kb, int row, uint32_t bytes) {
        mbar_wait(emptyB + s * 8, ph, ab);
        if (elect_one()) { mbar_expect_tx(fullB + s * 8, bytes); tma_load(sb + OFF_B + s * B_SLOT, map, kb * 64, row, fullB + s * 8); }
        __syncwarp();
        if (++s == SB) { s = 0; ph ^= 1; }
      };
      auto load = [&](const CUtensorMap* map, int nk, int row, uint32_t bytes) {
#pragma unroll 1
        for (int kb = 0; kb < nk; kb++) load1(map, kb, row, bytes);
      };
      auto dep = [&](int c, unsigned n) { cnt_wait_warp(c, ep1 * n, ab); fence_async_global(); };
#pragma unroll 1
      for (int l = 0; l < 2; l++) {
        if (l == 0) dep(C_PRO, NCTA);
#pragma unroll 1
        for (int kb = 0; kb < 10; kb++) { load1(&M.wq, kb, 240 * j, 10240); load1(&M.wq, kb, 240 * j + 80, 10240); }
        load(&M.wq, 10, 240 * j + 160, 10240);
        if (l == 0) dep(C_BGA, 272);
        load(&M.wo, 10, 80 * j, 10240);
        load(&M.wi, 10, 192 * j, 12288);
        load(&M.wi, 10, 192 * j + 96, 12288);
        dep(C_Z2 + l * 8 + j, 32);
        load(&M.z, 32, 96 * j, 12288);
        if (l == 0) dep(C_BGB, 80);
        load(&M.wout, 12, 80 * j, 10240);
      }
    } else if (warp < 12) {
      const int gw = 2 * b + (warp - 10);
#pragma unroll 1
      for (int u = gw; u < 352; u += 256) {
        if (u < 80) transpose_strip(P.wo, 640, 640, 8 * u, g_Wo, 8 * u, nullptr, lane);
        else if (u < 272) {
          const int n = 8 * (u - 80), m = n < 768 ? n : n - 768;
          transpose_strip(P.win, 1536, 640, n, g_Wi, 192 * (m / 96) + (n < 768 ? 96 : 0) + m % 96, g_csi, lane);
        } else transpose_strip(P.wout, 640, 768, 8 * (u - 272), g_Wout, 8 * (u - 272), nullptr, lane);
        __threadfence();
        __syncwarp();
        if (lane == 0) cnt_add(u < 272 ? C_BGA : C_BGB);
      }
      if (warp == 10 && lane < 16)
        asm volatile("cp.async.bulk.prefetch.L2.global [%0], %1;" :: "l"(P.wsp + (size_t)(128 * r + 16 * j + lane) * S_), "r"(4096) : "memory");
    }
  } else {
    asm volatile("setmaxnreg.inc.sync.aligned.u32 224;");
    const int wg = warp >> 2, w4 = warp & 3;
    Pipe p;
    p.ab = ab; p.fullA = fullA; p.emptyA = emptyA; p.fullB = fullB; p.emptyB = emptyB;
    p.dA = make_desc(sb + OFF_A + wg * 8192, 16, 1024, 1); p.dB = make_desc(sb + OFF_B, 16, 1024, 1);
    p.sa = 0; p.sb = 0; p.pa = 0; p.pb = 0; p.leader = (threadIdx.x & 127) == 0;

    const uint32_t sb_ = sb;
    const int lane_ = lane;
    prologue(P, b, r, j, sb + OFF_STG, warp, lane);
    bar_sync(3, 256);
    if (threadIdx.x == 0) { __threadfence(); cnt_add(C_PRO); }
    PROF(1);

#pragma unroll 1
    for (int l = 0; l < 2; l++) {
      constexpr float LOG2E = 1.4426950408889634f;
      const uint32_t sb = uniform(sb_);
      const int lane = opaque(lane_), g = lane >> 2, q = lane & 3;
      const int rl = 64 * wg + 16 * w4 + g;
      const int row0 = 128 * r + rl;
      const uint32_t stg = sb + OFF_STG + wg * STG_WG;
      const uint32_t statS = sb + OFF_STAT + wg * 512;
      {
        float ak[40], av[40], aq[40];
        gemm2<80, 10>(ak, av, p);
        PROF(2 + l * 24);
        if (l == 0) {
          if (threadIdx.x < 240) {
            float s = 0.f;
#pragma unroll
            for (int k = 0; k < 20; k++) s += __ldcg(&g_csq_part[k * 1920 + 240 * j + threadIdx.x]);
            asm volatile("st.shared.f32 [%0], %1;" :: "r"(sb + OFF_CSQ + threadIdx.x * 4), "f"(s) : "memory");
          }
          bar_sync(3, 256);
        }
        gemm1<80, 10>(aq, p);
        PROF(3 + l * 24);
        float m0, r0, m1, r1;
        row_stats(g_xstat + ((l == 0 ? 0 : 2) * 16 + r) * 1024, rl, q, 1.f / 640.f, m0, r0, m1, r1);
        const int rw = 16 * w4 + g;
        bar_sync(3, 256);
        {
          const uint32_t pv = stg + VS_OFF + q * VS_HS + rw * 16;
          uint32_t v0[10], v1[10];
#pragma unroll
          for (int i = 0; i < 10; i++) {
            const float2 cv = lds64f(sb + OFF_CSQ + (80 + 8 * i + 2 * q) * 4);
            v0[i] = pack2(r0 * (av[4 * i] - m0 * cv.x), r0 * (av[4 * i + 1] - m0 * cv.y));
            v1[i] = pack2(r1 * (av[4 * i + 2] - m1 * cv.x), r1 * (av[4 * i + 3] - m1 * cv.y));
          }
          sts128(pv, v0[0], v0[1], v0[2], v0[3]); sts128(pv + 1024, v0[4], v0[5], v0[6], v0[7]); sts128(pv + 2048, v0[8], v0[9], 0x00003f80u, 0u);
          sts128(pv + 128, v1[0], v1[1], v1[2], v1[3]); sts128(pv + 128 + 1024, v1[4], v1[5], v1[6], v1[7]); sts128(pv + 128 + 2048, v1[8], v1[9], 0x00003f80u, 0u);
        }
        feature_rows(ak, sb + OFF_CSQ, q, r0 * LOG2E, m0, r1 * LOG2E, m1, stg + q * PHK_HS + rw * 16);
        fence_async_smem();
        bar_sync(3, 256);
        {
          float kv0[12], kv1[12];
          const uint32_t s0 = sb + OFF_STG;
          fresh(kv0); fresh(kv1);
          wg_fence();
#pragma unroll
          for (int half = 0; half < 2; half++) {
#pragma unroll
            for (int s = 0; s < 4; s++) {
              const uint32_t base = s0 + half * STG_WG + s * 256;
              wgmma<24, 1, 1>(kv0, make_desc(base + (2 * wg) * PHK_HS, 128, 1024, 0), make_desc(base + VS_OFF + (2 * wg) * VS_HS, 128, 1024, 0), half + s > 0);
              wgmma<24, 1, 1>(kv1, make_desc(base + (2 * wg + 1) * PHK_HS, 128, 1024, 0), make_desc(base + VS_OFF + (2 * wg + 1) * VS_HS, 128, 1024, 0), half + s > 0);
            }
          }
          wg_commit();
          wg_wait<0>();
          pin(kv0); pin(kv1);
          bar_sync(3, 256);
          const uint32_t ks = stg + KVS_OFF;
          const int f0 = 16 * w4 + g;
#pragma unroll
          for (int i = 0; i < 3; i++) {
#pragma unroll
            for (int e = 0; e < 2; e++) {
              const int d = 8 * i + 2 * q + e;
              if (f0 < 40) { sts32(ks + (d * 40 + f0) * 4, __float_as_uint(kv0[4 * i + e])); sts32(ks + 3840 + (d * 40 + f0) * 4, __float_as_uint(kv1[4 * i + e])); }
              if (f0 + 8 < 40) { sts32(ks + (d * 40 + f0 + 8) * 4, __float_as_uint(kv0[4 * i + 2 + e])); sts32(ks + 3840 + (d * 40 + f0 + 8) * 4, __float_as_uint(kv1[4 * i + 2 + e])); }
            }
          }
          fence_async_smem();
          bar_sync(1 + wg, 128);
          if (w4 == 0) {
            if (elect_one()) {
              bulk_reduce_add_f32(g_kv + (l * 8 + j) * 3840 + wg * 1920, ks, 7680);
              bulk_commit_wait();
              cnt_add(C_KV + l * 8 + j);
            }
            __syncwarp();
          }
        }
        PROF(4 + l * 24);
        {
          const uint32_t pq = stg + q * PHQ_HS + rw * 16;
          feature_rows(aq, sb + OFF_CSQ + 160 * 4, q, r0 * LOG2E, m0, r1 * LOG2E, m1, pq);
          sts128(pq + 5 * 1024, 0u, 0u, 0u, 0u);
          sts128(pq + 5 * 1024 + 128, 0u, 0u, 0u, 0u);
        }
      }
      PROF(5 + l * 24);
      {
        cnt_wait_warp(C_KV + l * 8 + j, ep1 * 32, p.ab);
        PROF(6 + l * 24);
        const float* kvg = g_kv + (l * 8 + j) * 3840;
#pragma unroll
        for (int m = 0; m < 3; m++) {
          const int id = threadIdx.x + 256 * m;
          if (id < 576) {
            const int kc = id % 6, n = (id / 6) % 24, h = id / 144;
            uint32_t w0 = 0, w1 = 0, w2 = 0, w3 = 0;
            if (kc < 5) {
              const float4 a = __ldcg(reinterpret_cast<const float4*>(kvg + (h * 24 + n) * 40 + 8 * kc));
              const float4 c = __ldcg(reinterpret_cast<const float4*>(kvg + (h * 24 + n) * 40 + 8 * kc + 4));
              w0 = pack2(a.x, a.y); w1 = pack2(a.z, a.w); w2 = pack2(c.x, c.y); w3 = pack2(c.z, c.w);
            }
            sts128(sb + OFF_STG + (h >> 1) * STG_WG + KVS_OFF + (h & 1) * 2304 + (n >> 3) * 768 + kc * 128 + (n & 7) * 16, w0, w1, w2, w3);
          }
        }
        fence_async_smem();
        bar_sync(3, 256);
        float o0[12], o1[12], o2[12], o3[12];
        fresh(o0); fresh(o1); fresh(o2); fresh(o3);
        wg_fence();
#pragma unroll
        for (int s = 0; s < 3; s++) {
          const uint32_t kb0 = sb + OFF_STG + KVS_OFF + s * 256, kb1 = kb0 + STG_WG;
          wgmma<24, 0, 0>(o0, make_desc(stg + 0 * PHQ_HS + s * 2048, 1024, 128, 0), make_desc(kb0, 128, 768, 0), s > 0);
          wgmma<24, 0, 0>(o1, make_desc(stg + 1 * PHQ_HS + s * 2048, 1024, 128, 0), make_desc(kb0 + 2304, 128, 768, 0), s > 0);
          wgmma<24, 0, 0>(o2, make_desc(stg + 2 * PHQ_HS + s * 2048, 1024, 128, 0), make_desc(kb1, 128, 768, 0), s > 0);
          wgmma<24, 0, 0>(o3, make_desc(stg + 3 * PHQ_HS + s * 2048, 1024, 128, 0), make_desc(kb1 + 2304, 128, 768, 0), s > 0);
        }
        wg_commit();
        wg_wait<0>();
        pin(o0); pin(o1); pin(o2); pin(o3);
        bar_sync(1 + wg, 128);
        const int rw = 16 * w4 + g;
        auto emit = [&](const float (&o)[12], int h) {
          const float d0 = rcp(__shfl_sync(0xffffffffu, o[8], (lane & ~3) | 2) + 1e-6f);
          const float d1 = rcp(__shfl_sync(0xffffffffu, o[10], (lane & ~3) | 2) + 1e-6f);
          const uint32_t a0 = stg + rw * 160 + (20 * h + 2 * q) * 2, a1 = a0 + 8 * 160;
          sts32(a0, pack2(o[0] * d0, o[1] * d0)); sts32(a1, pack2(o[2] * d1, o[3] * d1));
          sts32(a0 + 16, pack2(o[4] * d0, o[5] * d0)); sts32(a1 + 16, pack2(o[6] * d1, o[7] * d1));
          if (q < 2) { sts32(a0 + 32, pack2(o[8] * d0, o[9] * d0)); sts32(a1 + 32, pack2(o[10] * d1, o[11] * d1)); }
        };
        emit(o0, 0); emit(o1, 1); emit(o2, 2); emit(o3, 3);
        fence_async_smem();
        bar_sync(1 + wg, 128);
        if (w4 == 0) {
          if (elect_one()) {
            tma_store2(&M.sAct, stg, 80 * j, 128 * r + 64 * wg);
            bulk_commit_wait();
            cnt_add(C_O + l * 32 + 2 * r + wg);
          }
          __syncwarp();
        }
      }
      PROF(7 + l * 24);
      {
        uint32_t res[20];
        load_resid(res, l == 0 ? P.x : g_act + 2 * S_ * D_, row0, 80 * j, q);
        float acc[40];
        gemm1<80, 10>(acc, p);
        PROF(8 + l * 24);
        const int buf = l == 0 ? 1 : 3;
        resid_epilogue(acc, res, stg, statS, wg, w4, lane, &M.sAct, 80 * j, buf * S_ + 128 * r + 64 * wg,
                       g_xstat + (buf * 16 + r) * 1024 + j * 128 + 64 * wg, C_X1 + l * 32 + 2 * r + wg);
      }
      PROF(9 + l * 24);
      uint32_t z1[24];
      {
        float a2[48], a1[48];
        gemm1<96, 10>(a2, p);
        PROF(10 + l * 24);
        if (l == 0) {
          if (threadIdx.x < 192) {
            const float s = __ldcg(&g_csi[192 * j + threadIdx.x]);
            asm volatile("st.shared.f32 [%0], %1;" :: "r"(sb + OFF_CSI + threadIdx.x * 4), "f"(s) : "memory");
          }
          bar_sync(3, 256);
        }
        gemm1<96, 10>(a1, p);
        PROF(11 + l * 24);
        float m0, r0, m1, r1;
        row_stats(g_xstat + ((l == 0 ? 1 : 3) * 16 + r) * 1024, rl, q, 1.f / 640.f, m0, r0, m1, r1);
        uint32_t z2[24];
        float s0 = 0.f, t0 = 0.f, s1 = 0.f, t1 = 0.f;
#pragma unroll
        for (int i = 0; i < 12; i++) {
          const float2 c = lds64f(sb + OFF_CSI + (8 * i + 2 * q) * 4);
          z2[2 * i] = pack2(gelu(r0 * (a2[4 * i] - m0 * c.x)), gelu(r0 * (a2[4 * i + 1] - m0 * c.y)));
          z2[2 * i + 1] = pack2(gelu(r1 * (a2[4 * i + 2] - m1 * c.x)), gelu(r1 * (a2[4 * i + 3] - m1 * c.y)));
          const float a = bf_lo(z2[2 * i]), bb = bf_hi(z2[2 * i]), cc = bf_lo(z2[2 * i + 1]), d = bf_hi(z2[2 * i + 1]);
          s0 += a + bb; t0 = fmaf(a, a, fmaf(bb, bb, t0)); s1 += cc + d; t1 = fmaf(cc, cc, fmaf(d, d, t1));
        }
#pragma unroll
        for (int m = 1; m <= 2; m <<= 1) {
          s0 += __shfl_xor_sync(0xffffffffu, s0, m); t0 += __shfl_xor_sync(0xffffffffu, t0, m);
          s1 += __shfl_xor_sync(0xffffffffu, s1, m); t1 += __shfl_xor_sync(0xffffffffu, t1, m);
        }
        bar_sync(1 + wg, 128);
        const int rw = 16 * w4 + g;
        if (q == 0) { sts64f(statS + rw * 8, s0, t0); sts64f(statS + (rw + 8) * 8, s1, t1); }
        fence_async_smem();
        bar_sync(1 + wg, 128);
        if (w4 == 0) {
          if (elect_one()) {
            bulk_store(g_zstat + (l * 16 + r) * 1024 + j * 128 + 64 * wg, statS, 512);
            bulk_commit_wait();
            cnt_add(C_ZS + l * 32 + 2 * r + wg);
          }
          __syncwarp();
        }
#pragma unroll
        for (int i = 0; i < 12; i++) {
          const float2 c = lds64f(sb + OFF_CSI + (96 + 8 * i + 2 * q) * 4);
          z1[2 * i] = pack2(gelu(r0 * (a1[4 * i] - m0 * c.x)), gelu(r0 * (a1[4 * i + 1] - m0 * c.y)));
          z1[2 * i + 1] = pack2(gelu(r1 * (a1[4 * i + 2] - m1 * c.x)), gelu(r1 * (a1[4 * i + 3] - m1 * c.y)));
        }
        PROF(12 + l * 24);
        cnt_wait_warp(C_ZS + l * 32 + 2 * r + wg, ep1 * 8, p.ab);
        PROF(13 + l * 24);
        float zm0, zr0, zm1, zr1;
        row_stats(g_zstat + (l * 16 + r) * 1024, rl, q, 1.f / 768.f, zm0, zr0, zm1, zr1);
        const int mi = lane >> 3, fr = lane & 7;
#pragma unroll
        for (int i = 0; i < 12; i += 2) {
          uint32_t n[4];
#pragma unroll
          for (int u = 0; u < 2; u++) {
            n[2 * u] = pack2((bf_lo(z2[2 * (i + u)]) - zm0) * zr0, (bf_hi(z2[2 * (i + u)]) - zm0) * zr0);
            n[2 * u + 1] = pack2((bf_lo(z2[2 * (i + u) + 1]) - zm1) * zr1, (bf_hi(z2[2 * (i + u) + 1]) - zm1) * zr1);
          }
          const int f = 8 * (i + (mi >> 1)) + fr, sc = 2 * w4 + (mi & 1);
          stsm4t(stg + f * 128 + ((sc ^ (f & 7)) << 4), n[0], n[1], n[2], n[3]);
        }
        fence_async_smem();
        bar_sync(1 + wg, 128);
        if (w4 == 0) {
          if (elect_one()) {
            tma_store2(&M.sZ, stg, 128 * r + 64 * wg, 96 * j);
            bulk_commit_wait();
            cnt_add(C_Z2 + l * 8 + j);
          }
          __syncwarp();
        }
      }
      PROF(14 + l * 24);
      {
        const float bs0 = __bfloat162float(P.bsp[row0]), bs1 = __bfloat162float(P.bsp[row0 + 8]);
        float acc[48];
        gemm1<96, 32>(acc, p);
        PROF(15 + l * 24);
        bar_sync(1 + wg, 128);
        const int rr = 16 * w4 + (lane & 15);
#pragma unroll
        for (int i = 0; i < 12; i += 2) {
          uint32_t n[4];
#pragma unroll
          for (int u = 0; u < 2; u++) {
            const int t = i + u;
            n[2 * u] = pack2(bf_lo(z1[2 * t]) * (acc[4 * t] + bs0), bf_hi(z1[2 * t]) * (acc[4 * t + 1] + bs0));
            n[2 * u + 1] = pack2(bf_lo(z1[2 * t + 1]) * (acc[4 * t + 2] + bs1), bf_hi(z1[2 * t + 1]) * (acc[4 * t + 3] + bs1));
          }
          const int ct = i + (lane >> 4);
          stsm4(stg + (ct >> 2) * 4096 + rr * 64 + (((ct & 3) ^ ((rr >> 1) & 3)) << 4), n[0], n[1], n[2], n[3]);
        }
        fence_async_smem();
        bar_sync(1 + wg, 128);
        if (w4 == 0) {
          if (elect_one()) {
            tma_store3(&M.sH, stg, 0, 128 * r + 64 * wg, 3 * j);
            bulk_commit_wait();
            cnt_add(C_H + l * 32 + 2 * r + wg);
          }
          __syncwarp();
        }
      }
      PROF(16 + l * 24);
      {
        uint32_t res[20];
        load_resid(res, g_act + (l == 0 ? 1 : 3) * S_ * D_, row0, 80 * j, q);
        float acc[40];
        gemm1<80, 12>(acc, p);
        PROF(17 + l * 24);
        if (l == 0)
          resid_epilogue(acc, res, stg, statS, wg, w4, lane, &M.sAct, 80 * j, 2 * S_ + 128 * r + 64 * wg,
                         g_xstat + (2 * 16 + r) * 1024 + j * 128 + 64 * wg, C_X2 + 2 * r + wg);
        else
          resid_epilogue(acc, res, stg, statS, wg, w4, lane, &M.sOut, 80 * j, 128 * r + 64 * wg, nullptr, -1);
      }
      PROF(18 + l * 24);
    }
    if (b == 0 && threadIdx.x == 0) *(volatile unsigned*)&g_epoch = ep1;
  }
}

typedef CUresult (*EncodeFn)(CUtensorMap*, CUtensorMapDataType, cuuint32_t, void*, const cuuint64_t*, const cuuint64_t*, const cuuint32_t*,
                             const cuuint32_t*, CUtensorMapInterleave, CUtensorMapSwizzle, CUtensorMapL2promotion, CUtensorMapFloatOOBfill);

CUtensorMap map2d(EncodeFn fn, const void* ptr, uint64_t rows, uint64_t cols, uint32_t box_rows, uint32_t box_cols, CUtensorMapSwizzle sw) {
  CUtensorMap m;
  cuuint64_t dims[2] = {cols, rows}, strides[1] = {cols * 2};
  cuuint32_t box[2] = {box_cols, box_rows}, es[2] = {1, 1};
  fn(&m, CU_TENSOR_MAP_DATA_TYPE_BFLOAT16, 2, const_cast<void*>(ptr), dims, strides, box, es, CU_TENSOR_MAP_INTERLEAVE_NONE, sw,
     CU_TENSOR_MAP_L2_PROMOTION_L2_256B, CU_TENSOR_MAP_FLOAT_OOB_FILL_NONE);
  return m;
}

}

extern "C" void kernel_launch(void* const* d_in, const int* in_sizes, int n_in, void* d_out, int out_size) {
  (void)in_sizes; (void)n_in; (void)out_size;
  static bool init = false;
  static Maps M;
  static Params P;
  static void* cached_ptrs[10];
  bool same = init;
  for (int i = 0; i < 9 && same; i++) same = cached_ptrs[i] == d_in[i];
  same = same && cached_ptrs[9] == d_out;
  if (!same) {
    void* fp = nullptr;
    cudaDriverEntryPointQueryResult st;
    cudaGetDriverEntryPoint("cuTensorMapEncodeTiled", &fp, cudaEnableDefault, &st);
    EncodeFn fn = (EncodeFn)fp;
    void *act, *h, *z, *wq, *wo, *wi, *wout;
    cudaGetSymbolAddress(&act, g_act); cudaGetSymbolAddress(&h, g_h); cudaGetSymbolAddress(&z, g_z);
    cudaGetSymbolAddress(&wq, g_Wq); cudaGetSymbolAddress(&wo, g_Wo); cudaGetSymbolAddress(&wi, g_Wi); cudaGetSymbolAddress(&wout, g_Wout);
    const CUtensorMapSwizzle S128 = CU_TENSOR_MAP_SWIZZLE_128B;
    M.x0 = map2d(fn, d_in[0], 2048, 640, 128, 64, S128);
    M.act = map2d(fn, act, 4 * 2048, 640, 128, 64, S128);
    M.wsp = map2d(fn, d_in[6], 2048, 2048, 128, 64, S128);
    M.h = map2d(fn, h, 2048, 768, 128, 64, S128);
    M.wq = map2d(fn, wq, 1920, 640, 80, 64, S128);
    M.wo = map2d(fn, wo, 640, 640, 80, 64, S128);
    M.wi = map2d(fn, wi, 1536, 640, 96, 64, S128);
    M.z = map2d(fn, z, 768, 2048, 96, 64, S128);
    M.wout = map2d(fn, wout, 640, 768, 80, 64, S128);
    M.sAct = map2d(fn, act, 4 * 2048, 640, 64, 80, CU_TENSOR_MAP_SWIZZLE_NONE);
    M.sOut = map2d(fn, d_out, 2048, 640, 64, 80, CU_TENSOR_MAP_SWIZZLE_NONE);
    M.sZ = map2d(fn, z, 768, 2048, 96, 64, S128);
    {
      cuuint64_t dims[3] = {32, 2048, 24}, strides[2] = {768 * 2, 64};
      cuuint32_t box[3] = {32, 64, 3}, es[3] = {1, 1, 1};
      fn(&M.sH, CU_TENSOR_MAP_DATA_TYPE_BFLOAT16, 3, h, dims, strides, box, es, CU_TENSOR_MAP_INTERLEAVE_NONE, CU_TENSOR_MAP_SWIZZLE_64B,
         CU_TENSOR_MAP_L2_PROMOTION_NONE, CU_TENSOR_MAP_FLOAT_OOB_FILL_NONE);
    }
    P.x = (const __nv_bfloat16*)d_in[0]; P.wqkv = (const __nv_bfloat16*)d_in[1]; P.wphi = (const __nv_bfloat16*)d_in[2];
    P.wo = (const __nv_bfloat16*)d_in[3]; P.win = (const __nv_bfloat16*)d_in[5]; P.wsp = (const __nv_bfloat16*)d_in[6];
    P.bsp = (const __nv_bfloat16*)d_in[7]; P.wout = (const __nv_bfloat16*)d_in[8];
    cudaFuncSetAttribute(mega_kernel, cudaFuncAttributeMaxDynamicSharedMemorySize, SMEM_BYTES);
    for (int i = 0; i < 9; i++) cached_ptrs[i] = d_in[i];
    cached_ptrs[9] = d_out;
    init = true;
  }
  mega_kernel<<<NCTA, NTHREADS, SMEM_BYTES>>>(M, P, (__nv_bfloat16*)d_out);
}
```

```cpp
#include <cuda_runtime.h>
#include <cuda_bf16.h>
#include <cuda.h>
#include <stdint.h>

namespace {

constexpr int S_ = 2048, D_ = 640, FH_ = 768;
constexpr int NCTA = 128;
constexpr int NTHREADS = 384;

constexpr int SA = 5, SB = 6;
constexpr int A_SLOT = 16384, B_SLOT = 12288;
constexpr int OFF_A = 0;
constexpr int OFF_B = OFF_A + SA * A_SLOT;
constexpr int OFF_STG = OFF_B + SB * B_SLOT;
constexpr int STG_WG = 33792;
constexpr int OFF_MISC = OFF_STG + 2 * STG_WG;
constexpr int OFF_BAR = OFF_MISC;
constexpr int BAR_STREADY = 22, BAR_STFREE = 24, BAR_XSTAT = 26, BAR_ZSTAT = 28, BAR_KV = 30, BAR_PRO = 31, BAR_TR = 32, BAR_TR2 = 33, BAR_IN = 34;
constexpr int OFF_ABORT = OFF_MISC + 288;
constexpr int OFF_CSQ = OFF_MISC + 320;
constexpr int OFF_CSI = OFF_CSQ + 240 * 4;
constexpr int OFF_STAT = OFF_MISC + 2048;
constexpr int OFF_XRS = OFF_STAT + 1024;
constexpr int OFF_ZRS = OFF_XRS + 1024;
constexpr int SMEM_USED = OFF_ZRS + 1024;
constexpr int SMEM_BYTES = SMEM_USED + 1024;
constexpr int PRO_W = OFF_B;
constexpr int PRO_CS = PRO_W + 20480;
constexpr int PRO_XS = PRO_CS + 1280;
constexpr int PRO_ZERO = PRO_XS + 1024;
constexpr int PRO_PHI = PRO_ZERO + 1920;
constexpr int PRO_IN = PRO_PHI + 16 * 1152;
constexpr int PRO_PITCH = 656;
constexpr int TR_IN = OFF_STG, TR_OUT = OFF_STG + 32768;
static_assert(PRO_IN + 32 * PRO_PITCH <= OFF_STG, "prologue staging");
static_assert(OFF_STG % 1024 == 0 && STG_WG % 1024 == 0, "staging alignment");
static_assert(OFF_CSI + 192 * 4 <= OFF_STAT, "misc overlap");
static_assert(SMEM_BYTES <= 232448, "smem budget");
constexpr int PHK_HS = 5 * 1024 + 32;
constexpr int VS_OFF = 4 * PHK_HS;
constexpr int VS_HS = 3 * 1024 + 32;
constexpr int PHQ_HS = 6 * 1024 + 32;
constexpr int KVS_OFF = 4 * PHQ_HS;
static_assert(VS_OFF + 4 * VS_HS <= STG_WG && KVS_OFF + 7680 <= STG_WG && KVS_OFF % 128 == 0, "staging layout");

__device__ __nv_bfloat16 g_Wq[1920 * 640];
__device__ float g_csq[2 * 1920];
__device__ __nv_bfloat16 g_Wo[640 * 640];
__device__ __nv_bfloat16 g_Wi[1536 * 640];
__device__ float g_csi[2 * 1536];
__device__ __nv_bfloat16 g_Wout[640 * 768];
__device__ __nv_bfloat16 g_act[4 * S_ * D_];
__device__ __nv_bfloat16 g_h[S_ * FH_];
__device__ __nv_bfloat16 g_z[FH_ * S_];
__device__ float2 g_xstat[4 * 16 * 8 * 128];
__device__ float2 g_zstat[2 * 16 * 8 * 128];
__device__ float g_kv[2 * 8 * 3840];
constexpr int C_PRO = 0, C_BGA = 1, C_BGB = 2;
constexpr int C_KV = 3;
constexpr int C_Z2 = C_KV + 16;
constexpr int C_O = C_Z2 + 16;
constexpr int C_X1 = C_O + 64;
constexpr int C_ZS = C_X1 + 64;
constexpr int C_H = C_ZS + 64;
constexpr int C_X2 = C_H + 64;
constexpr int C_NUM = C_X2 + 32;
__device__ unsigned g_cnt[C_NUM * 32];
__device__ unsigned g_epoch;
#define PROF(i)
#define PROFW(i)
#define PROFG(i)
#define PROF2(i)

struct Maps {
  CUtensorMap x0, act, wsp, h, wq, wo, wi, z, wout;
  CUtensorMap lWo, lWi, lWout;
  CUtensorMap rX0;
  CUtensorMap sAct, sOut, sH, sZ, sWq, sWo, sWi, sWout;
};

__device__ __forceinline__ uint32_t smem_u32(const void* p) { return (uint32_t)__cvta_generic_to_shared(p); }
__device__ __forceinline__ uint32_t uniform(uint32_t x) {
  uint32_t y; asm volatile("mov.u32 %0, %1;" : "=r"(y) : "r"(x)); return __shfl_sync(0xffffffffu, y, 0);
}
__device__ __forceinline__ uint32_t opaque(uint32_t x) { uint32_t y; asm volatile("mov.u32 %0, %1;" : "=r"(y) : "r"(x)); return y; }
__device__ __forceinline__ bool elect_one() {
  uint32_t p; asm volatile("{ .reg .pred P; elect.sync _|P, 0xffffffff; selp.u32 %0, 1, 0, P; }" : "=r"(p)); return p;
}
__device__ __forceinline__ void mbar_init(uint32_t bar, uint32_t cnt) { asm volatile("mbarrier.init.shared::cta.b64 [%0], %1;" :: "r"(bar), "r"(cnt) : "memory"); }
__device__ __forceinline__ void mbar_expect_tx(uint32_t bar, uint32_t bytes) { asm volatile("mbarrier.arrive.expect_tx.shared::cta.b64 _, [%0], %1;" :: "r"(bar), "r"(bytes) : "memory"); }
__device__ __forceinline__ void mbar_arrive(uint32_t bar) { asm volatile("mbarrier.arrive.shared::cta.b64 _, [%0];" :: "r"(bar) : "memory"); }
__device__ __forceinline__ bool mbar_try(uint32_t bar, uint32_t parity) {
  uint32_t ok;
  asm volatile("{ .reg .pred p; mbarrier.try_wait.parity.shared::cta.b64 p, [%1], %2; selp.u32 %0, 1, 0, p; }" : "=r"(ok) : "r"(bar), "r"(parity) : "memory");
  return ok;
}
__device__ __forceinline__ uint32_t lds32v(uint32_t a) { uint32_t v; asm volatile("ld.volatile.shared.u32 %0, [%1];" : "=r"(v) : "r"(a) : "memory"); return v; }
__device__ __forceinline__ void mbar_wait(uint32_t bar, uint32_t parity, uint32_t abort_addr) {
  if (__builtin_expect(!mbar_try(bar, parity), 0)) {
    uint32_t n = 0;
#pragma unroll 1
    while (!mbar_try(bar, parity)) {
      if (lds32v(abort_addr) != 0) break;
      if (++n > (1u << 20)) { asm volatile("st.volatile.shared.u32 [%0], 1;" :: "r"(abort_addr) : "memory"); break; }
    }
  }
}
__device__ __forceinline__ void tma_load(uint32_t dst, const CUtensorMap* map, int c0, int c1, uint32_t bar) {
  asm volatile("cp.async.bulk.tensor.2d.shared::cluster.global.mbarrier::complete_tx::bytes [%0], [%1, {%3, %4}], [%2];"
               :: "r"(dst), "l"(map), "r"(bar), "r"(c0), "r"(c1) : "memory");
}
__device__ __forceinline__ void tma_store2(const CUtensorMap* map, uint32_t src, int c0, int c1) {
  asm volatile("cp.async.bulk.tensor.2d.global.shared::cta.bulk_group [%0, {%2, %3}], [%1];" :: "l"(map), "r"(src), "r"(c0), "r"(c1) : "memory");
}
__device__ __forceinline__ void tma_store3(const CUtensorMap* map, uint32_t src, int c0, int c1, int c2) {
  asm volatile("cp.async.bulk.tensor.3d.global.shared::cta.bulk_group [%0, {%2, %3, %4}], [%1];" :: "l"(map), "r"(src), "r"(c0), "r"(c1), "r"(c2) : "memory");
}
__device__ __forceinline__ void bulk_store(void* dst, uint32_t src, uint32_t bytes) {
  asm volatile("cp.async.bulk.global.shared::cta.bulk_group [%0], [%1], %2;" :: "l"(dst), "r"(src), "r"(bytes) : "memory");
}
__device__ __forceinline__ void bulk_reduce_add_f32(void* dst, uint32_t src, uint32_t bytes) {
  asm volatile("cp.reduce.async.bulk.global.shared::cta.bulk_group.add.f32 [%0], [%1], %2;" :: "l"(dst), "r"(src), "r"(bytes) : "memory");
}
__device__ __forceinline__ void bulk_commit_wait() {
  asm volatile("cp.async.bulk.commit_group;" ::: "memory");
  asm volatile("cp.async.bulk.wait_group 0;" ::: "memory");
}
__device__ __forceinline__ void fence_async_smem() { asm volatile("fence.proxy.async.shared::cta;" ::: "memory"); }
__device__ __forceinline__ void fence_async_global() { asm volatile("fence.proxy.async.global;" ::: "memory"); }
__device__ __forceinline__ void bar_sync(int id, int n) { asm volatile("bar.sync %0, %1;" :: "r"(id), "r"(n) : "memory"); }
__device__ __forceinline__ void cnt_add(int idx) { asm volatile("red.relaxed.gpu.global.add.u32 [%0], 1;" :: "l"(&g_cnt[idx * 32]) : "memory"); }
__device__ __forceinline__ void cnt_wait(int idx, unsigned target, uint32_t abort_addr) {
  asm volatile("{\n .reg .pred p;\n .reg .u32 n, v, a;\n mov.u32 n, 0;\n"
               "LAB_WAIT:\n ld.relaxed.gpu.global.u32 v, [%0];\n sub.u32 v, v, %1;\n setp.ge.s32 p, v, 0;\n @p bra LAB_DONE;\n"
               " ld.volatile.shared.u32 a, [%2];\n setp.ne.u32 p, a, 0;\n @p bra LAB_DONE;\n"
               " add.u32 n, n, 1;\n setp.lt.u32 p, n, 1048576;\n @p bra LAB_WAIT;\n"
               " st.volatile.shared.u32 [%2], 1;\n LAB_DONE:\n }"
               :: "l"(&g_cnt[idx * 32]), "r"(target), "r"(abort_addr) : "memory");
}
__device__ __forceinline__ void cnt_wait_warp(int idx, unsigned target, uint32_t abort_addr) {
  if ((threadIdx.x & 31) == 0) cnt_wait(idx, target, abort_addr);
  __syncwarp();
}
__device__ __forceinline__ uint64_t make_desc(uint32_t saddr, uint32_t lbo, uint32_t sbo, uint64_t layout) {
  return (uint64_t)((saddr & 0x3FFFF) >> 4) | ((uint64_t)(lbo >> 4) << 16) | ((uint64_t)(sbo >> 4) << 32) | (layout << 62);
}
__device__ __forceinline__ void wg_fence() { asm volatile("wgmma.fence.sync.aligned;" ::: "memory"); }
__device__ __forceinline__ void wg_commit() { asm volatile("wgmma.commit_group.sync.aligned;" ::: "memory"); }
template <int N> __device__ __forceinline__ void wg_wait() { asm volatile("wgmma.wait_group.sync.aligned %0;" :: "n"(N) : "memory"); }
template <int N> __device__ __forceinline__ void fresh(float (&a)[N]) {
#pragma unroll
  for (int i = 0; i < N; i++) asm volatile("mov.b32 %0, 0;" : "=f"(a[i]));
}
template <int N> __device__ __forceinline__ void pin(float (&a)[N]) {
#pragma unroll
  for (int i = 0; i < N; i++) asm volatile("" : "+f"(a[i]) :: "memory");
}
__device__ __forceinline__ uint32_t pack2(float lo, float hi) {
  uint32_t r; asm("cvt.rn.bf16x2.f32 %0, %1, %2;" : "=r"(r) : "f"(hi), "f"(lo)); return r;
}
__device__ __forceinline__ float bf_lo(uint32_t v) { return __uint_as_float(v << 16); }
__device__ __forceinline__ float bf_hi(uint32_t v) { return __uint_as_float(v & 0xffff0000u); }
__device__ __forceinline__ float ex2(float x) { float y; asm("ex2.approx.ftz.f32 %0, %1;" : "=f"(y) : "f"(x)); return y; }
__device__ __forceinline__ float rcp(float x) { float y; asm("rcp.approx.ftz.f32 %0, %1;" : "=f"(y) : "f"(x)); return y; }
__device__ __forceinline__ void sts128(uint32_t a, uint32_t x, uint32_t y, uint32_t z, uint32_t w) {
  asm volatile("st.shared.v4.u32 [%0], {%1, %2, %3, %4};" :: "r"(a), "r"(x), "r"(y), "r"(z), "r"(w) : "memory");
}
__device__ __forceinline__ void sts32(uint32_t a, uint32_t x) { asm volatile("st.shared.u32 [%0], %1;" :: "r"(a), "r"(x) : "memory"); }
__device__ __forceinline__ void sts64f(uint32_t a, float x, float y) { asm volatile("st.shared.v2.f32 [%0], {%1, %2};" :: "r"(a), "f"(x), "f"(y) : "memory"); }
__device__ __forceinline__ float2 lds64f(uint32_t a) { float2 v; asm volatile("ld.shared.v2.f32 {%0, %1}, [%2];" : "=f"(v.x), "=f"(v.y) : "r"(a)); return v; }
__device__ __forceinline__ void stsm4(uint32_t a, uint32_t r0, uint32_t r1, uint32_t r2, uint32_t r3) {
  asm volatile("stmatrix.sync.aligned.m8n8.x4.shared.b16 [%0], {%1, %2, %3, %4};" :: "r"(a), "r"(r0), "r"(r1), "r"(r2), "r"(r3) : "memory");
}
__device__ __forceinline__ void stsm4t(uint32_t a, uint32_t r0, uint32_t r1, uint32_t r2, uint32_t r3) {
  asm volatile("stmatrix.sync.aligned.m8n8.x4.trans.shared.b16 [%0], {%1, %2, %3, %4};" :: "r"(a), "r"(r0), "r"(r1), "r"(r2), "r"(r3) : "memory");
}
__device__ __forceinline__ void mma16816(float (&c)[4], const uint32_t (&a)[4], uint32_t b0, uint32_t b1) {
  asm volatile("mma.sync.aligned.m16n8k16.row.col.f32.bf16.bf16.f32 {%0, %1, %2, %3}, {%4, %5, %6, %7}, {%8, %9}, {%0, %1, %2, %3};"
               : "+f"(c[0]), "+f"(c[1]), "+f"(c[2]), "+f"(c[3]) : "r"(a[0]), "r"(a[1]), "r"(a[2]), "r"(a[3]), "r"(b0), "r"(b1));
}

template <int TA, int TB>
__device__ __forceinline__ void wgmma_n24(float (&d)[12], uint64_t da, uint64_t db, int scale_d) {
  asm volatile("{ .reg .pred p; setp.ne.b32 p, %14, 0; "
    "wgmma.mma_async.sync.aligned.m64n24k16.f32.bf16.bf16 "
    "{%0, %1, %2, %3, %4, %5, %6, %7, %8, %9, %10, %11}, "
    "%12, %13, p, 1, 1, %15, %16; }"
    : "+f"(d[0]), "+f"(d[1]), "+f"(d[2]), "+f"(d[3]), "+f"(d[4]), "+f"(d[5]), "+f"(d[6]), "+f"(d[7]), "+f"(d[8]), "+f"(d[9]), "+f"(d[10]), "+f"(d[11])
    : "l"(da), "l"(db), "r"(scale_d), "n"(TA), "n"(TB));
}
template <int TA, int TB>
__device__ __forceinline__ void wgmma_n80(float (&d)[40], uint64_t da, uint64_t db, int scale_d) {
  asm volatile("{ .reg .pred p; setp.ne.b32 p, %42, 0; "
    "wgmma.mma_async.sync.aligned.m64n80k16.f32.bf16.bf16 "
    "{%0, %1, %2, %3, %4, %5, %6, %7, %8, %9, %10, %11, %12, %13, %14, %15, %16, %17, %18, %19, %20, %21, %22, %23, %24, %25, %26, %27, %28, %29, %30, %31, %32, %33, %34, %35, %36, %37, %38, %39}, "
    "%40, %41, p, 1, 1, %43, %44; }"
    : "+f"(d[0]), "+f"(d[1]), "+f"(d[2]), "+f"(d[3]), "+f"(d[4]), "+f"(d[5]), "+f"(d[6]), "+f"(d[7]), "+f"(d[8]), "+f"(d[9]), "+f"(d[10]), "+f"(d[11]), "+f"(d[12]), "+f"(d[13]), "+f"(d[14]), "+f"(d[15]), "+f"(d[16]), "+f"(d[17]), "+f"(d[18]), "+f"(d[19]), "+f"(d[20]), "+f"(d[21]), "+f"(d[22]), "+f"(d[23]), "+f"(d[24]), "+f"(d[25]), "+f"(d[26]), "+f"(d[27]), "+f"(d[28]), "+f"(d[29]), "+f"(d[30]), "+f"(d[31]), "+f"(d[32]), "+f"(d[33]), "+f"(d[34]), "+f"(d[35]), "+f"(d[36]), "+f"(d[37]), "+f"(d[38]), "+f"(d[39])
    : "l"(da), "l"(db), "r"(scale_d), "n"(TA), "n"(TB));
}
template <int TA, int TB>
__device__ __forceinline__ void wgmma_n96(float (&d)[48], uint64_t da, uint64_t db, int scale_d) {
  asm volatile("{ .reg .pred p; setp.ne.b32 p, %50, 0; "
    "wgmma.mma_async.sync.aligned.m64n96k16.f32.bf16.bf16 "
    "{%0, %1, %2, %3, %4, %5, %6, %7, %8, %9, %10, %11, %12, %13, %14, %15, %16, %17, %18, %19, %20, %21, %22, %23, %24, %25, %26, %27, %28, %29, %30, %31, %32, %33, %34, %35, %36, %37, %38, %39, %40, %41, %42, %43, %44, %45, %46, %47}, "
    "%48, %49, p, 1, 1, %51, %52; }"
    : "+f"(d[0]), "+f"(d[1]), "+f"(d[2]), "+f"(d[3]), "+f"(d[4]), "+f"(d[5]), "+f"(d[6]), "+f"(d[7]), "+f"(d[8]), "+f"(d[9]), "+f"(d[10]), "+f"(d[11]), "+f"(d[12]), "+f"(d[13]), "+f"(d[14]), "+f"(d[15]), "+f"(d[16]), "+f"(d[17]), "+f"(d[18]), "+f"(d[19]), "+f"(d[20]), "+f"(d[21]), "+f"(d[22]), "+f"(d[23]), "+f"(d[24]), "+f"(d[25]), "+f"(d[26]), "+f"(d[27]), "+f"(d[28]), "+f"(d[29]), "+f"(d[30]), "+f"(d[31]), "+f"(d[32]), "+f"(d[33]), "+f"(d[34]), "+f"(d[35]), "+f"(d[36]), "+f"(d[37]), "+f"(d[38]), "+f"(d[39]), "+f"(d[40]), "+f"(d[41]), "+f"(d[42]), "+f"(d[43]), "+f"(d[44]), "+f"(d[45]), "+f"(d[46]), "+f"(d[47])
    : "l"(da), "l"(db), "r"(scale_d), "n"(TA), "n"(TB));
}

template <int N, int TA, int TB>
__device__ __forceinline__ void wgmma(float (&d)[N / 2], uint64_t da, uint64_t db, int s) {
  if constexpr (N == 24) wgmma_n24<TA, TB>(d, da, db, s);
  else if constexpr (N == 80) wgmma_n80<TA, TB>(d, da, db, s);
  else wgmma_n96<TA, TB>(d, da, db, s);
}

struct Pipe {
  uint32_t fullA, emptyA, fullB, emptyB, ab;
  uint64_t dA, dB;
  int sa, sb;
  uint32_t pa, pb;
  bool leader;
  __device__ __forceinline__ void advA() { if (++sa == SA) { sa = 0; pa ^= 1; } }
  __device__ __forceinline__ void advB() { if (++sb == SB) { sb = 0; pb ^= 1; } }
};

template <int N>
__device__ __forceinline__ void gemm1(float (&acc)[N / 2], Pipe& p, int NK) {
  int ra = 0, rb = 0;
  fresh(acc);
#pragma unroll 1
  for (int kb = 0; kb < NK; kb++) {
    mbar_wait(p.fullB + p.sb * 8, p.pb, p.ab);
    mbar_wait(p.fullA + p.sa * 8, p.pa, p.ab);
    wg_fence();
    const uint64_t da = p.dA + (uint64_t)(p.sa * (A_SLOT >> 4)), db = p.dB + (uint64_t)(p.sb * (B_SLOT >> 4));
#pragma unroll
    for (int k = 0; k < 4; k++) wgmma<N, 0, 0>(acc, da + k * 2, db + k * 2, (kb > 0 || k > 0) ? 1 : 0);
    wg_commit();
    wg_wait<1>();
    if (kb > 0 && p.leader) { mbar_arrive(p.emptyA + ra * 8); mbar_arrive(p.emptyB + rb * 8); }
    ra = p.sa; rb = p.sb;
    p.advA(); p.advB();
  }
  wg_wait<0>();
  pin(acc);
  if (p.leader) { mbar_arrive(p.emptyA + ra * 8); mbar_arrive(p.emptyB + rb * 8); }
}
__device__ __forceinline__ void feature_rows(float (&acc)[40], uint32_t cs_addr, float m0, float r0, float m1, float r1, uint32_t addr, bool pad) {
  constexpr float LOG2E = 1.4426950408889634f;
  float nm = -m0, a = r0 * LOG2E;
#pragma unroll 1
  for (int h = 0; h < 2; h++) {
    float u[20];
#pragma unroll
    for (int i = 0; i < 10; i++) {
      const float2 c = lds64f(cs_addr + i * 32);
      u[2 * i] = fmaf(nm, c.x, acc[4 * i]); u[2 * i + 1] = fmaf(nm, c.y, acc[4 * i + 1]);
      acc[4 * i] = acc[4 * i + 2]; acc[4 * i + 1] = acc[4 * i + 3];
    }
    float mx[2], mn[2];
#pragma unroll
    for (int k = 0; k < 2; k++) { mx[k] = fmaxf(u[k], u[k + 2]); mn[k] = fminf(u[k], u[k + 2]); }
#pragma unroll
    for (int f = 4; f < 20; f++) { mx[f & 1] = fmaxf(mx[f & 1], u[f]); mn[f & 1] = fminf(mn[f & 1], u[f]); }
    const float bp = -a * fmaxf(mx[0], mx[1]), bn = a * fminf(mn[0], mn[1]);
    float ep[20], en[20], sp[2], sn[2];
#pragma unroll
    for (int f = 0; f < 20; f++) {
      ep[f] = ex2(fmaf(u[f], a, bp));
      en[f] = ex2(fmaf(u[f], -a, bn));
      if (f < 2) { sp[f] = ep[f]; sn[f] = en[f]; } else { sp[f & 1] += ep[f]; sn[f & 1] += en[f]; }
    }
    const float rp = rcp(sp[0] + sp[1]), rn = rcp(sn[0] + sn[1]);
    uint32_t w[20];
#pragma unroll
    for (int f = 0; f < 10; f++) { w[f] = pack2(ep[2 * f] * rp, ep[2 * f + 1] * rp); w[10 + f] = pack2(en[2 * f] * rn, en[2 * f + 1] * rn); }
#pragma unroll
    for (int c = 0; c < 5; c++) sts128(addr + c * 1024, w[4 * c], w[4 * c + 1], w[4 * c + 2], w[4 * c + 3]);
    if (pad) sts128(addr + 5 * 1024, 0u, 0u, 0u, 0u);
    addr += 128; nm = -m1; a = r1 * LOG2E;
  }
}

struct GeluRow {
  float nm, A, B, H;
  __device__ __forceinline__ GeluRow(float m, float rs) : nm(-m), A(0.7978845608029f * rs), B(0.0356774081363f * rs * rs * rs), H(0.5f * rs) {}
  __device__ __forceinline__ float operator()(float acc, float c) const {
    const float y = fmaf(nm, c, acc);
    const float u = y * fmaf(y * y, B, A), hx = H * y;
    float t;
    asm("tanh.approx.f32 %0, %1;" : "=f"(t) : "f"(u));
    return fmaf(hx, t, hx);
  }
};
template <bool STATS>
__device__ __forceinline__ void gelu_rows(const float (&acc)[48], uint32_t cs_addr, float m0, float r0, float m1, float r1,
                                          uint32_t (&za)[12], uint32_t (&zb)[12], uint32_t stat_addr, bool stat_lane) {
  const GeluRow g0(m0, r0), g1(m1, r1);
  float s0 = 0.f, t0 = 0.f, s1 = 0.f, t1 = 0.f;
#pragma unroll
  for (int i = 0; i < 12; i++) {
    const float2 c = lds64f(cs_addr + i * 32);
    za[i] = pack2(g0(acc[4 * i], c.x), g0(acc[4 * i + 1], c.y));
    zb[i] = pack2(g1(acc[4 * i + 2], c.x), g1(acc[4 * i + 3], c.y));
    if (STATS) {
      const float x = bf_lo(za[i]), y = bf_hi(za[i]), z = bf_lo(zb[i]), w = bf_hi(zb[i]);
      s0 += x + y; t0 = fmaf(x, x, fmaf(y, y, t0)); s1 += z + w; t1 = fmaf(z, z, fmaf(w, w, t1));
    }
  }
  if (STATS) {
#pragma unroll
    for (int m = 1; m <= 2; m <<= 1) {
      s0 += __shfl_xor_sync(0xffffffffu, s0, m); t0 += __shfl_xor_sync(0xffffffffu, t0, m);
      s1 += __shfl_xor_sync(0xffffffffu, s1, m); t1 += __shfl_xor_sync(0xffffffffu, t1, m);
    }
    if (stat_lane) { sts64f(stat_addr, s0, t0); sts64f(stat_addr + 64, s1, t1); }
  }
}

struct Stage {
  uint32_t ready, freeb, ab, ph;
  __device__ __forceinline__ void acquire() { mbar_wait(freeb, ph, ab); ph ^= 1; }
  __device__ __forceinline__ void publish() {
    fence_async_smem();
    __syncwarp();
    if ((threadIdx.x & 31) == 0) mbar_arrive(ready);
  }
};

struct Params {
  const __nv_bfloat16 *x, *wqkv, *wphi, *wo, *win, *wsp, *bsp, *wout;
};

__device__ __forceinline__ void cp16(uint32_t dst, const void* src) { asm volatile("cp.async.cg.shared.global [%0], [%1], 16;" :: "r"(dst), "l"(src) : "memory"); }
__device__ __forceinline__ uint32_t lds32(uint32_t a) { uint32_t v; asm volatile("ld.shared.u32 %0, [%1];" : "=r"(v) : "r"(a)); return v; }

struct TrUnit { int which, k0, n0, drow; };
__device__ __forceinline__ TrUnit tr_unit(int u) {
  TrUnit t;
  t.which = u < 200 ? 0 : u < 680 ? 1 : 2;
  const int v = u - (t.which == 0 ? 0 : t.which == 1 ? 200 : 680), nk = t.which == 2 ? 12 : 10;
  t.k0 = 64 * (v % nk); t.n0 = 32 * (v / nk);
  const int m = t.n0 < 768 ? t.n0 : t.n0 - 768;
  t.drow = t.which == 1 ? 192 * (m / 96) + (t.n0 < 768 ? 96 : 0) + m % 96 : t.n0;
  return t;
}

__device__ __forceinline__ void prologue(const Params& P, int b, int r, int j, uint32_t sb, int warp, int lane) {
  const int g = lane >> 2, q = lane & 3, t256 = threadIdx.x;
  const bool fold = b < 120;
  const int kr = b % 20, cg = b / 20, t = cg >> 1, hb = 16 * (cg & 1);
  if (fold) {
#pragma unroll
    for (int i = 0; i < 5; i++) {
      const int c = t256 + 256 * i, row = c / 40, ch = c % 40;
      cp16(sb + PRO_IN + row * PRO_PITCH + ch * 16, P.wqkv + (size_t)(32 * kr + row) * 1920 + 640 * t + 20 * hb + 8 * ch);
    }
    if (t < 2) {
#pragma unroll 1
      for (int c = t256; c < 1600; c += 256) {
        const int row = c / 5, pc = c % 5, h = row / 20, d = row % 20;
        asm volatile("cp.async.ca.shared.global [%0], [%1], 8;" :: "r"(sb + PRO_PHI + h * 1152 + d * 48 + pc * 8), "l"(P.wphi + (size_t)hb * 400 + c * 4) : "memory");
      }
      if (t256 < 192) sts128(sb + PRO_PHI + (t256 / 12) * 1152 + 960 + (t256 % 12) * 16, 0u, 0u, 0u, 0u);
    }
  }
#pragma unroll
  for (int i = 0; i < 5; i++) {
    const int c = t256 + 256 * i, row = c / 10, ch = c % 10;
    cp16(sb + PRO_W + c * 16, P.x + (size_t)(128 * r + row) * D_ + 80 * j + 8 * ch);
  }
  asm volatile("cp.async.commit_group;" ::: "memory");
  if (t256 < 120) sts128(sb + PRO_ZERO + t256 * 16, 0u, 0u, 0u, 0u);
  asm volatile("cp.async.wait_group 0;" ::: "memory");
  PROF(64 + 56);
  if (lane == 0) mbar_arrive(sb + OFF_BAR + BAR_IN * 8);
  bar_sync(3, 256);
  {
    float s = 0.f, tt = 0.f;
#pragma unroll
    for (int i = 0; i < 5; i++) {
      uint32_t w[4];
      asm volatile("ld.shared.v4.u32 {%0, %1, %2, %3}, [%4];" : "=r"(w[0]), "=r"(w[1]), "=r"(w[2]), "=r"(w[3]) : "r"(sb + PRO_W + t256 * 80 + i * 16));
#pragma unroll
      for (int c = 0; c < 4; c++) { const float a = bf_lo(w[c]), bb = bf_hi(w[c]); s += a + bb; tt = fmaf(a, a, fmaf(bb, bb, tt)); }
    }
    s += __shfl_xor_sync(0xffffffffu, s, 1); tt += __shfl_xor_sync(0xffffffffu, tt, 1);
    if ((t256 & 1) == 0) sts64f(sb + PRO_XS + (t256 >> 1) * 8, s, tt);
  }
  bar_sync(3, 256);
  PROF(64 + 50);
  if (fold) {
#pragma unroll 1
    for (int hh = 0; hh < 2; hh++) {
      const int hl = 2 * warp + hh, d0 = 2 * q;
      uint32_t a0[2][4], a1[2][4], bw[4][3];
      if (t < 2) {
        const uint32_t ph = sb + PRO_PHI + hl * 1152, r8 = lane & 7, m = lane >> 3;
        asm volatile("ldmatrix.sync.aligned.m8n8.x4.trans.shared.b16 {%0, %1, %2, %3}, [%4];" : "=r"(a0[0][0]), "=r"(a0[0][1]), "=r"(a0[0][2]), "=r"(a0[0][3])
                     : "r"(ph + (8 * (m >> 1) + r8) * 48 + (m & 1) * 16));
        asm volatile("ldmatrix.sync.aligned.m8n8.x4.trans.shared.b16 {%0, %1, %2, %3}, [%4];" : "=r"(a1[0][0]), "=r"(a1[0][1]), "=r"(a0[1][0]), "=r"(a0[1][2])
                     : "r"(ph + (m < 2 ? (16 + r8) * 48 + m * 16 : (8 * (m - 2) + r8) * 48 + 32)));
        asm volatile("ldmatrix.sync.aligned.m8n8.x1.trans.shared.b16 {%0}, [%1];" : "=r"(a1[1][0]) : "r"(ph + (16 + r8) * 48 + 32));
      } else {
        auto one = [&](int f, int d) -> uint32_t { return (f == d ? 0x3f80u : 0u) | (f == d + 1 ? 0x3f800000u : 0u); };
        a0[0][0] = one(g, d0); a0[0][1] = one(g + 8, d0); a0[0][2] = one(g, d0 + 8); a0[0][3] = one(g + 8, d0 + 8);
        a1[0][0] = 0u; a1[0][1] = 0u; a0[1][0] = 0u; a0[1][2] = 0u; a1[1][0] = q < 2 ? one(g + 16, d0 + 16) : 0u;
      }
      a1[0][2] = a1[0][3] = 0u; a0[1][1] = a0[1][3] = 0u; a1[1][1] = a1[1][2] = a1[1][3] = 0u;
#pragma unroll
      for (int nt = 0; nt < 4; nt++) {
        const uint32_t pw = sb + PRO_IN + (8 * nt + g) * PRO_PITCH + (20 * hl + 2 * q) * 2;
        bw[nt][0] = lds32(pw); bw[nt][1] = lds32(pw + 16); bw[nt][2] = q < 2 ? lds32(pw + 32) : 0u;
      }
      float c[2][4][4];
#pragma unroll
      for (int mt = 0; mt < 2; mt++)
#pragma unroll
        for (int nt = 0; nt < 4; nt++) {
          c[mt][nt][0] = c[mt][nt][1] = c[mt][nt][2] = c[mt][nt][3] = 0.f;
          mma16816(c[mt][nt], a0[mt], bw[nt][0], bw[nt][1]);
        }
#pragma unroll
      for (int mt = 0; mt < 2; mt++)
#pragma unroll
        for (int nt = 0; nt < 4; nt++) mma16816(c[mt][nt], a1[mt], bw[nt][2], 0u);
      const int n0 = 80 * (hl >> 2) + 8 * (g >> 1) + 2 * (hl & 3) + (g & 1);
      float cs[3] = {0.f, 0.f, 0.f};
#pragma unroll
      for (int nt = 0; nt < 4; nt++) {
        const uint32_t w0 = pack2(c[0][nt][0], c[0][nt][1]), w1 = pack2(c[0][nt][2], c[0][nt][3]), w2 = pack2(c[1][nt][0], c[1][nt][1]);
        cs[0] += bf_lo(w0) + bf_hi(w0); cs[1] += bf_lo(w1) + bf_hi(w1); cs[2] += bf_lo(w2) + bf_hi(w2);
        const uint32_t a = sb + PRO_W + n0 * 64 + (8 * nt + 2 * q) * 2;
        sts32(a, w0); sts32(a + 32 * 64, w1);
        if (g < 4) sts32(a + 64 * 64, w2);
      }
#pragma unroll
      for (int k = 0; k < 3; k++) { cs[k] += __shfl_xor_sync(0xffffffffu, cs[k], 1); cs[k] += __shfl_xor_sync(0xffffffffu, cs[k], 2); }
      if (q == 0) {
        sts32(sb + PRO_CS + n0 * 4, __float_as_uint(cs[0])); sts32(sb + PRO_CS + (n0 + 32) * 4, __float_as_uint(cs[1]));
        if (g < 4) sts32(sb + PRO_CS + (n0 + 64) * 4, __float_as_uint(cs[2]));
      }
      PROF(64 + 30 + hh);
    }
  }
  fence_async_smem();
  __syncwarp();
  if (lane == 0) mbar_arrive(sb + OFF_BAR + BAR_PRO * 8);
  PROF(64 + 52);
  if (b + 128 * warp < 920) {
    const int m = lane >> 3, row = lane & 7;
    float cs[4] = {0.f, 0.f, 0.f, 0.f};
    mbar_wait(sb + OFF_BAR + BAR_TR * 8, 0, sb + OFF_ABORT);
#pragma unroll
    for (int a = 0; a < 8; a++) {
      uint32_t r0, r1, r2, r3;
      asm volatile("ldmatrix.sync.aligned.m8n8.x4.trans.shared.b16 {%0, %1, %2, %3}, [%4];" : "=r"(r0), "=r"(r1), "=r"(r2), "=r"(r3)
                   : "r"(sb + TR_IN + warp * 4096 + (8 * a + row) * 64 + ((m ^ ((row >> 1) & 3)) << 4)));
      stsm4(sb + TR_OUT + warp * 4096 + (8 * m + row) * 128 + ((a ^ row) << 4), r0, r1, r2, r3);
      cs[0] += bf_lo(r0) + bf_hi(r0); cs[1] += bf_lo(r1) + bf_hi(r1); cs[2] += bf_lo(r2) + bf_hi(r2); cs[3] += bf_lo(r3) + bf_hi(r3);
    }
#pragma unroll
    for (int c = 0; c < 4; c++) {
      cs[c] += __shfl_xor_sync(0xffffffffu, cs[c], 1); cs[c] += __shfl_xor_sync(0xffffffffu, cs[c], 2);
      if (q == 0) sts32(sb + OFF_ZRS + warp * 128 + (8 * c + g) * 4, __float_as_uint(cs[c]));
    }
    fence_async_smem();
  }
  __syncwarp();
  if (lane == 0) mbar_arrive(sb + OFF_BAR + BAR_TR2 * 8);
}

__global__ void __launch_bounds__(NTHREADS, 1) mega_kernel(const __grid_constant__ Maps M, const Params P) {
  extern __shared__ uint8_t smem_raw[];
  const uint32_t sb = uniform((smem_u32(smem_raw) + 1023) & ~1023u);
  const int warp = uniform(threadIdx.x >> 5), lane = threadIdx.x & 31;
  const int b = uniform(blockIdx.x), r = b >> 3, j = b & 7;
  const uint32_t bars = sb + OFF_BAR;
  const uint32_t fullA = bars, emptyA = fullA + SA * 8, fullB = emptyA + SA * 8, emptyB = fullB + SB * 8;
  const uint32_t ab = sb + OFF_ABORT;
  PROF(0);
  PROFG(64 + 60);
  if (threadIdx.x == 0) {
    asm volatile("st.shared.u32 [%0], 0;" :: "r"(ab) : "memory");
    for (int s = 0; s < SA; s++) { mbar_init(fullA + s * 8, 1); mbar_init(emptyA + s * 8, 2); }
    for (int s = 0; s < SB; s++) { mbar_init(fullB + s * 8, 1); mbar_init(emptyB + s * 8, 2); }
    for (int w = 0; w < 2; w++) {
      mbar_init(bars + (BAR_STREADY + w) * 8, 4); mbar_init(bars + (BAR_STFREE + w) * 8, 1);
      mbar_init(bars + (BAR_XSTAT + w) * 8, 1); mbar_init(bars + (BAR_ZSTAT + w) * 8, 1);
    }
    mbar_init(bars + BAR_KV * 8, 2); mbar_init(bars + BAR_PRO * 8, 8); mbar_init(bars + BAR_TR * 8, 1); mbar_init(bars + BAR_TR2 * 8, 8); mbar_init(bars + BAR_IN * 8, 8);
    asm volatile("fence.mbarrier_init.release.cluster;" ::: "memory");
  }
  __syncthreads();

  if (warp >= 8) {
    asm volatile("setmaxnreg.dec.sync.aligned.u32 104;");
    unsigned ep1;
    asm volatile("ld.relaxed.gpu.global.u32 %0, [%1];" : "=r"(ep1) : "l"(&g_epoch) : "memory");
    if (warp == 8) {
      int s = 0, pf = 0; uint32_t ph = 1;
#pragma unroll 1
      for (int seg = 0; seg < 10; seg++) {
        const int l = seg >= 5, sg = seg - 5 * l;
        const CUtensorMap* map = sg == 0 ? (l == 0 ? &M.x0 : &M.act) : sg == 3 ? &M.wsp : sg == 4 ? &M.h : &M.act;
        const int row = 128 * r + (sg == 0 ? l * 2 * S_ : sg == 2 ? (l == 0 ? 1 : 3) * S_ : 0);
        const int nk = sg == 3 ? 32 : sg == 4 ? 12 : 10, reps = sg == 0 ? 3 : sg == 2 ? 2 : 1;
        const int dep = sg == 0 ? (l == 0 ? -1 : C_X2) : sg == 1 ? C_O + l * 32 : sg == 2 ? C_X1 + l * 32 : sg == 4 ? C_H + l * 32 : -1;
        if (dep >= 0) {
          if (lane < 2) cnt_wait(dep + 2 * r + lane, (ep1 + 1) * 8, ab);
          __syncwarp();
          fence_async_global();
          PROFW(64 + (seg == 5 ? 48 : seg == 6 ? 44 : seg == 7 ? 45 : seg == 9 ? 47 : 62));
        }
#pragma unroll 1
        for (int i = 0, kb = 0; i < nk * reps; i++) {
          mbar_wait(emptyA + s * 8, ph, ab);
          if (elect_one()) {
            mbar_expect_tx(fullA + s * 8, A_SLOT); tma_load(sb + OFF_A + s * A_SLOT, map, kb * 64, row, fullA + s * 8);
            if (pf < 32 && (seg > 0 || i >= 5)) asm volatile("cp.async.bulk.prefetch.L2.global [%0], %1;" :: "l"(P.wsp + (size_t)(128 * r + 16 * j) * S_ + pf * 1024), "r"(2048) : "memory");
          }
          __syncwarp();
          pf += (seg > 0 || i >= 5);
          if (++kb == nk) kb = 0;
          if (++s == SA) { s = 0; ph ^= 1; }
        }
      }
    } else if (warp == 9) {
      int s = 0; uint32_t ph = 1;
#pragma unroll 1
      for (int seg = 0; seg < 16; seg++) {
        const int l = seg >> 3, sg = seg & 7;
        const CUtensorMap* map = sg < 3 ? &M.wq : sg == 3 ? &M.wo : sg < 6 ? &M.wi : sg == 6 ? &M.z : &M.wout;
        const int row = sg < 3 ? 240 * j + 80 * sg : sg == 3 || sg == 7 ? 80 * j : sg < 6 ? 192 * j + 96 * (sg - 4) : 96 * j;
        const int nk = sg == 6 ? 32 : sg == 7 ? 12 : 10;
        const uint32_t bytes = sg >= 4 && sg <= 6 ? 12288 : 10240;
        int dep = -1; unsigned n = 0;
        if (sg == 6) { dep = C_Z2 + l * 8 + j; n = 32; }
        else if (l == 0) {
          if (sg == 0) { dep = C_PRO; n = NCTA; } else if (sg == 3) { dep = C_BGA; n = 680; } else if (sg == 7) { dep = C_BGB; n = 240; }
        }
        if (dep >= 0) { cnt_wait_warp(dep, (ep1 + 1) * n, ab); fence_async_global(); PROFW(64 + (seg == 0 ? 55 : seg == 3 ? 57 : seg == 14 ? 46 : 62)); }
#pragma unroll 1
        for (int kb = 0; kb < nk; kb++) {
          mbar_wait(emptyB + s * 8, ph, ab);
          if (elect_one()) { mbar_expect_tx(fullB + s * 8, bytes); tma_load(sb + OFF_B + s * B_SLOT, map, kb * 64, row, fullB + s * 8); }
          __syncwarp();
          if (++s == SB) { s = 0; ph ^= 1; }
        }
      }
    } else {
      const int hw = warp - 10;
      const uint32_t stg = sb + OFF_STG + hw * STG_WG, statS = sb + OFF_STAT + hw * 512;
      const uint32_t ready = bars + (BAR_STREADY + hw) * 8, freeb = bars + (BAR_STFREE + hw) * 8;
      const int rowt = 128 * r + 64 * hw;
      if (hw == 0 && lane < (int)(sizeof(Maps) / sizeof(CUtensorMap)))
        asm volatile("prefetch.tensormap [%0];" :: "l"(reinterpret_cast<const CUtensorMap*>(&M) + lane) : "memory");
      if (hw == 1) {
        const int u = b + 128 * lane;
        if (lane == 0) mbar_expect_tx(bars + BAR_TR * 8, ((920 - b + 127) >> 7) * 4096);
        if (lane < 4) sts128(sb + OFF_STAT + 896 + lane * 16, 0u, 0u, 0u, 0u);
        fence_async_smem();
        mbar_wait(bars + BAR_IN * 8, 0, ab);
        if (lane < 8 && u < 920) {
          const TrUnit t = tr_unit(u);
          tma_load(sb + TR_IN + lane * 4096, t.which == 0 ? &M.lWo : t.which == 1 ? &M.lWi : &M.lWout, t.n0, t.k0, bars + BAR_TR * 8);
        }
      }
      if (hw == 0) {
        mbar_wait(bars + BAR_PRO * 8, 0, ab);
        PROFW(64 + 35);
        if (elect_one()) {
          if (b < 120) {
            const int kr = b % 20, cg = b / 20, t = cg >> 1, part = t == 1 ? 0 : (t == 2 ? 1 : 2);
#pragma unroll 1
            for (int gi = 0; gi < 4; gi++) {
              const int n = 240 * (4 * (cg & 1) + gi) + 80 * part;
              tma_store2(&M.sWq, sb + PRO_W + gi * 5120, 32 * kr, n);
              bulk_reduce_add_f32(g_csq + (ep1 & 1) * 1920 + n, sb + PRO_CS + gi * 320, 320);
            }
          }
          bulk_store(g_xstat + r * 1024 + j * 128, sb + PRO_XS, 1024);
          bulk_store(g_kv + b * 480, sb + PRO_ZERO, 1920);
          if (b < 120) bulk_store(g_csq + ((ep1 & 1) ^ 1) * 1920 + 16 * b, sb + PRO_ZERO, 64);
          bulk_commit_wait();
          cnt_add(C_PRO);
        }
        __syncwarp();
        PROFW(64 + 53);
      }
      uint32_t rph = 0;
#pragma unroll 1
      for (int it = 0; it < 15; it++) {
        const int l = it >= 8, jb = it == 0 ? 6 : it - 1 - 7 * l;
        const int lr = l * 32 + 2 * r + hw;
        const int xb = it == 0 ? 0 : jb == 2 ? (l == 0 ? 1 : 3) : 2;
        int cnt = -1;
        if (jb == 0) cnt = C_KV + l * 8 + j; else if (jb == 1) cnt = C_O + lr; else if (jb == 2) cnt = C_X1 + lr; else if (jb == 3) cnt = C_ZS + lr;
        else if (jb == 4) cnt = C_Z2 + l * 8 + j; else if (jb == 5) cnt = C_H + lr; else if (l == 0) cnt = C_X2 + 2 * r + hw;
        float2* xst = g_xstat + (xb * 16 + r) * 1024 + 64 * hw;
        float2* zst = g_zstat + (l * 16 + r) * 1024 + 64 * hw;
        if (it > 0) {
          mbar_wait(ready, rph, ab); rph ^= 1;
          if (elect_one()) {
            if (jb == 0) bulk_reduce_add_f32(g_kv + (l * 8 + j) * 3840 + hw * 1920, stg + KVS_OFF, 7680);
            else if (jb == 3) bulk_store(zst + j * 128, statS, 512);
            else if (jb == 4) tma_store2(&M.sZ, stg, rowt, 96 * j);
            else if (jb == 5) tma_store3(&M.sH, stg, 0, rowt, 3 * j);
            else if (jb == 6 && l == 1) tma_store2(&M.sOut, stg, 80 * j, rowt);
            else {
              tma_store2(&M.sAct, stg, 80 * j, (jb == 1 ? 0 : xb * S_) + rowt);
              if (jb != 1) bulk_store(xst + j * 128, statS, 512);
            }
            asm volatile("cp.async.bulk.commit_group;" ::: "memory");
            asm volatile("cp.async.bulk.wait_group.read 0;" ::: "memory");
            if (jb == 1 || jb == 5) {
              const int hl = 2 * l + (jb == 5);
              mbar_expect_tx(freeb, 10240);
              tma_load(stg, hl == 0 ? &M.rX0 : &M.sAct, 80 * j, hl * S_ + rowt, freeb);
            } else mbar_arrive(freeb);
            asm volatile("cp.async.bulk.wait_group 0;" ::: "memory");
            if (cnt >= 0) cnt_add(cnt);
          }
          __syncwarp();
        }
        if (jb == 0) {
          cnt_wait_warp(cnt, (ep1 + 1) * 32, ab);
          const float* kvg = g_kv + (l * 8 + j) * 3840 + hw * 1920;
          float4 a[9], c[9];
#pragma unroll
          for (int m = 0; m < 9; m++) {
            const int id = lane + 32 * m, kc = id % 6, hn = id / 6;
            a[m] = make_float4(0.f, 0.f, 0.f, 0.f); c[m] = a[m];
            if (kc < 5) {
              a[m] = __ldcg(reinterpret_cast<const float4*>(kvg + hn * 40 + 8 * kc));
              c[m] = __ldcg(reinterpret_cast<const float4*>(kvg + hn * 40 + 8 * kc + 4));
            }
          }
#pragma unroll
          for (int m = 0; m < 9; m++) {
            const int id = lane + 32 * m, kc = id % 6, hn = id / 6, h = hn / 24, n = hn % 24;
            sts128(stg + KVS_OFF + h * 2304 + (n >> 3) * 768 + kc * 128 + (n & 7) * 16,
                   pack2(a[m].x, a[m].y), pack2(a[m].z, a[m].w), pack2(c[m].x, c[m].y), pack2(c[m].z, c[m].w));
          }
          fence_async_smem();
          __syncwarp();
          if (lane == 0) mbar_arrive(bars + BAR_KV * 8);
        } else if (jb == 2 || jb == 3 || (jb == 6 && l == 0)) {
          if (it == 0) {
            cnt_wait_warp(C_PRO, (ep1 + 1) * NCTA, ab);
#pragma unroll
            for (int c = 0; c < 8; c++)
              if (lane + 32 * c < 240) sts32(sb + OFF_CSQ + (lane + 32 * c) * 4, __float_as_uint(__ldcg(&g_csq[(ep1 & 1) * 1920 + 240 * j + lane + 32 * c])));
          } else cnt_wait_warp(cnt, (ep1 + 1) * 8, ab);
          if (it == 3) {
            cnt_wait_warp(C_BGA, (ep1 + 1) * 680, ab);
#pragma unroll
            for (int c = 0; c < 6; c++) sts32(sb + OFF_CSI + (lane + 32 * c) * 4, __float_as_uint(__ldcg(&g_csi[(ep1 & 1) * 1536 + 192 * j + lane + 32 * c])));
          }
          const float2* part = jb == 3 ? zst : xst;
          const float inv_n = jb == 3 ? 1.f / 768.f : 1.f / 640.f;
          const uint32_t dst = sb + (jb == 3 ? OFF_ZRS : OFF_XRS) + hw * 512;
          float2 v[2][8];
#pragma unroll
          for (int h = 0; h < 2; h++)
#pragma unroll
            for (int c = 0; c < 8; c++) v[h][c] = __ldcg(part + c * 128 + lane + 32 * h);
#pragma unroll
          for (int h = 0; h < 2; h++) {
            float s = 0.f, t = 0.f;
#pragma unroll
            for (int c = 0; c < 8; c++) { s += v[h][c].x; t += v[h][c].y; }
            const float m = s * inv_n;
            sts64f(dst + (lane + 32 * h) * 8, m, rsqrtf(fmaxf(t * inv_n - m * m, 0.f) + 1e-5f));
          }
          __syncwarp();
          if (lane == 0) mbar_arrive(bars + ((jb == 3 ? BAR_ZSTAT : BAR_XSTAT) + hw) * 8);
          if (it == 0 && hw == 1) {
            const int nu = (920 - b + 127) >> 7;
            const TrUnit t = tr_unit(min(b + 128 * (lane & 7), 919));
            mbar_wait(bars + BAR_TR2 * 8, 0, ab);
#pragma unroll 1
            for (int i = 0; i < nu; i++) {
              const int which = __shfl_sync(0xffffffffu, t.which, i), k0 = __shfl_sync(0xffffffffu, t.k0, i), drow = __shfl_sync(0xffffffffu, t.drow, i);
              if (elect_one()) {
                tma_store2(which == 0 ? &M.sWo : which == 1 ? &M.sWi : &M.sWout, sb + TR_OUT + i * 4096, k0, drow);
                if (which == 1) bulk_reduce_add_f32(g_csi + (ep1 & 1) * 1536 + drow, sb + OFF_ZRS + i * 128, 128);
                if (i == 0 && b < 96) bulk_store(g_csi + ((ep1 & 1) ^ 1) * 1536 + 16 * b, sb + OFF_STAT + 896, 64);
                asm volatile("cp.async.bulk.commit_group;" ::: "memory");
                asm volatile("cp.async.bulk.wait_group.read 0;" ::: "memory");
              }
              __syncwarp();
            }
            if (elect_one()) {
              mbar_arrive(bars + BAR_STFREE * 8); mbar_arrive(bars + (BAR_STFREE + 1) * 8);
              asm volatile("cp.async.bulk.wait_group 0;" ::: "memory");
#pragma unroll 1
              for (int i = 0; i < nu; i++) cnt_add(b + 128 * i < 680 ? C_BGA : C_BGB);
            }
            __syncwarp();
            PROFW(64 + 58);
          }
        }
      }
      if (b == 0 && hw == 0 && lane == 0) *(volatile unsigned*)&g_epoch = ep1 + 1;
      PROFW(64 + (hw == 0 ? 49 : 59));
    }
  } else {
    asm volatile("setmaxnreg.inc.sync.aligned.u32 200;");
    const int wg = warp >> 2, w4 = warp & 3;
    Pipe p;
    p.ab = ab; p.fullA = fullA; p.emptyA = emptyA; p.fullB = fullB; p.emptyB = emptyB;
    p.dA = make_desc(sb + OFF_A + wg * 8192, 16, 1024, 1); p.dB = make_desc(sb + OFF_B, 16, 1024, 1);
    p.sa = 0; p.sb = 0; p.pa = 0; p.pb = 0; p.leader = (threadIdx.x & 127) == 0;
    Stage st;
    st.ready = bars + (BAR_STREADY + wg) * 8; st.freeb = bars + (BAR_STFREE + wg) * 8; st.ab = ab; st.ph = 0;
    const uint32_t sb_ = sb;
    const int lane_ = lane;
    PROF(64 + 51);
    prologue(P, b, r, j, sb, warp, lane);
    PROF(1);

#pragma unroll 1
    for (int hl = 0; hl < 4; hl++) {
      const int l = hl >> 1;
      const uint32_t sb = uniform(sb_);
      const int lane = opaque(lane_), g = lane >> 2, q = lane & 3;
      const int rw = 16 * w4 + g;
      const int row0 = 128 * r + 64 * wg + rw;
      const uint32_t stg = sb + OFF_STG + wg * STG_WG;
      const uint32_t statS = sb + OFF_STAT + wg * 512;
      const uint32_t bars = sb + OFF_BAR;
      if ((hl & 1) == 0) {
        float m0, r0, m1, r1;
        {
          float ak[40], av[40], kv0[12], kv1[12];
          gemm1<80>(ak, p, 10);
          PROF(2 + l * 24);
          gemm1<80>(av, p, 10);
          PROF(3 + l * 24);
          mbar_wait(bars + (BAR_XSTAT + wg) * 8, 0, p.ab);
          const float2 sa = lds64f(sb + OFF_XRS + (64 * wg + rw) * 8), sc = lds64f(sb + OFF_XRS + (64 * wg + rw + 8) * 8);
          m0 = sa.x; r0 = sa.y; m1 = sc.x; r1 = sc.y;
          st.acquire();
          {
            const uint32_t pv = stg + VS_OFF + q * VS_HS + rw * 16;
            uint32_t v0[10], v1[10];
#pragma unroll
            for (int i = 0; i < 10; i++) {
              const float2 cv = lds64f(sb + OFF_CSQ + (80 + 8 * i + 2 * q) * 4);
              v0[i] = pack2(r0 * fmaf(-m0, cv.x, av[4 * i]), r0 * fmaf(-m0, cv.y, av[4 * i + 1]));
              v1[i] = pack2(r1 * fmaf(-m1, cv.x, av[4 * i + 2]), r1 * fmaf(-m1, cv.y, av[4 * i + 3]));
            }
            sts128(pv, v0[0], v0[1], v0[2], v0[3]); sts128(pv + 1024, v0[4], v0[5], v0[6], v0[7]); sts128(pv + 2048, v0[8], v0[9], 0x00003f80u, 0u);
            sts128(pv + 128, v1[0], v1[1], v1[2], v1[3]); sts128(pv + 128 + 1024, v1[4], v1[5], v1[6], v1[7]); sts128(pv + 128 + 2048, v1[8], v1[9], 0x00003f80u, 0u);
          }
          feature_rows(ak, sb + OFF_CSQ + q * 8, m0, r0, m1, r1, stg + q * PHK_HS + rw * 16, false);
          fresh(kv0); fresh(kv1);
          fence_async_smem();
          bar_sync(3, 256);
          PROF(19 + l * 24);
          const uint32_t s0 = sb + OFF_STG + 2 * wg * PHK_HS, s1 = sb + OFF_STG + VS_OFF + 2 * wg * VS_HS;
          wg_fence();
#pragma unroll
          for (int s = 0; s < 8; s++) {
            const uint32_t o = (s >> 2) * STG_WG + (s & 3) * 256;
            wgmma<24, 1, 1>(kv0, make_desc(s0 + o, 128, 1024, 0), make_desc(s1 + o, 128, 1024, 0), s > 0);
            wgmma<24, 1, 1>(kv1, make_desc(s0 + PHK_HS + o, 128, 1024, 0), make_desc(s1 + VS_HS + o, 128, 1024, 0), s > 0);
          }
          wg_commit();
          wg_wait<0>();
          pin(kv0); pin(kv1);
          bar_sync(3, 256);
          const uint32_t ks = stg + KVS_OFF + (2 * q * 40 + rw) * 4;
#pragma unroll
          for (int i = 0; i < 3; i++) {
#pragma unroll
            for (int e = 0; e < 2; e++) {
              const uint32_t a = ks + (8 * i + e) * 160;
              if (rw < 40) { sts32(a, __float_as_uint(kv0[4 * i + e])); sts32(a + 3840, __float_as_uint(kv1[4 * i + e])); }
              if (rw + 8 < 40) { sts32(a + 32, __float_as_uint(kv0[4 * i + 2 + e])); sts32(a + 3840 + 32, __float_as_uint(kv1[4 * i + 2 + e])); }
            }
          }
          st.publish();
        }
        PROF(20 + l * 24);
        {
          float aq[40];
          gemm1<80>(aq, p, 10);
          PROF(4 + l * 24);
          feature_rows(aq, sb + OFF_CSQ + 160 * 4 + q * 8, m0, r0, m1, r1, stg + q * PHQ_HS + rw * 16, true);
          fence_async_smem();
        }
        PROF(5 + l * 24);
        float o0[12], o1[12], o2[12], o3[12];
        fresh(o0); fresh(o1); fresh(o2); fresh(o3);
        bar_sync(1 + wg, 128);
        mbar_wait(bars + BAR_KV * 8, l, p.ab);
        PROF(6 + l * 24);
        wg_fence();
#pragma unroll
        for (int s = 0; s < 3; s++) {
          const uint32_t kb0 = sb + OFF_STG + KVS_OFF + s * 256, kb1 = kb0 + STG_WG;
          wgmma<24, 0, 0>(o0, make_desc(stg + 0 * PHQ_HS + s * 2048, 1024, 128, 0), make_desc(kb0, 128, 768, 0), s > 0);
          wgmma<24, 0, 0>(o1, make_desc(stg + 1 * PHQ_HS + s * 2048, 1024, 128, 0), make_desc(kb0 + 2304, 128, 768, 0), s > 0);
          wgmma<24, 0, 0>(o2, make_desc(stg + 2 * PHQ_HS + s * 2048, 1024, 128, 0), make_desc(kb1, 128, 768, 0), s > 0);
          wgmma<24, 0, 0>(o3, make_desc(stg + 3 * PHQ_HS + s * 2048, 1024, 128, 0), make_desc(kb1 + 2304, 128, 768, 0), s > 0);
        }
        wg_commit();
        wg_wait<0>();
        pin(o0); pin(o1); pin(o2); pin(o3);
        bar_sync(1 + wg, 128);
        st.acquire();
        auto emit = [&](const float (&o)[12], int h) {
          const float d0 = rcp(__shfl_sync(0xffffffffu, o[8], (lane & ~3) | 2) + 1e-6f);
          const float d1 = rcp(__shfl_sync(0xffffffffu, o[10], (lane & ~3) | 2) + 1e-6f);
          const uint32_t a0 = stg + rw * 160 + (20 * h + 2 * q) * 2, a1 = a0 + 8 * 160;
          sts32(a0, pack2(o[0] * d0, o[1] * d0)); sts32(a1, pack2(o[2] * d1, o[3] * d1));
          sts32(a0 + 16, pack2(o[4] * d0, o[5] * d0)); sts32(a1 + 16, pack2(o[6] * d1, o[7] * d1));
          if (q < 2) { sts32(a0 + 32, pack2(o[8] * d0, o[9] * d0)); sts32(a1 + 32, pack2(o[10] * d1, o[11] * d1)); }
        };
        emit(o0, 0); emit(o1, 1); emit(o2, 2); emit(o3, 3);
        st.publish();
        PROF(7 + l * 24);
      } else {
        float m0, r0, m1, r1;
        uint32_t z2a[12], z2b[12];
        {
          float a2[48];
          gemm1<96>(a2, p, 10);
          PROF(10 + l * 24);
          mbar_wait(bars + (BAR_XSTAT + wg) * 8, 1, p.ab);
          const float2 sa = lds64f(sb + OFF_XRS + (64 * wg + rw) * 8), sc = lds64f(sb + OFF_XRS + (64 * wg + rw + 8) * 8);
          m0 = sa.x; r0 = sa.y; m1 = sc.x; r1 = sc.y;
          st.acquire();
          gelu_rows<true>(a2, sb + OFF_CSI + q * 8, m0, r0, m1, r1, z2a, z2b, statS + rw * 8, q == 0);
          st.publish();
        }
        PROF(21 + l * 24);
        float a1[48];
        gemm1<96>(a1, p, 10);
        PROF(11 + l * 24);
        mbar_wait(bars + (BAR_ZSTAT + wg) * 8, l, p.ab);
        PROF(12 + l * 24);
        {
          const float2 a = lds64f(sb + OFF_ZRS + (64 * wg + rw) * 8), c = lds64f(sb + OFF_ZRS + (64 * wg + rw + 8) * 8);
          const float an = -a.x * a.y, cn = -c.x * c.y;
          st.acquire();
          const int mi = lane >> 3, fr = lane & 7;
          const uint32_t za = stg + (8 * (mi >> 1) + fr) * 128 + (((2 * w4 + (mi & 1)) ^ fr) << 4);
#pragma unroll
          for (int i = 0; i < 12; i += 2)
            stsm4t(za + i * 1024,
                   pack2(fmaf(bf_lo(z2a[i]), a.y, an), fmaf(bf_hi(z2a[i]), a.y, an)), pack2(fmaf(bf_lo(z2b[i]), c.y, cn), fmaf(bf_hi(z2b[i]), c.y, cn)),
                   pack2(fmaf(bf_lo(z2a[i + 1]), a.y, an), fmaf(bf_hi(z2a[i + 1]), a.y, an)), pack2(fmaf(bf_lo(z2b[i + 1]), c.y, cn), fmaf(bf_hi(z2b[i + 1]), c.y, cn)));
          st.publish();
        }
        PROF(13 + l * 24);
        uint32_t z1a[12], z1b[12];
        gelu_rows<false>(a1, sb + OFF_CSI + 96 * 4 + q * 8, m0, r0, m1, r1, z1a, z1b, 0, false);
        PROF(14 + l * 24);
        const float bs0 = __bfloat162float(P.bsp[row0]), bs1 = __bfloat162float(P.bsp[row0 + 8]);
        float acc[48];
        gemm1<96>(acc, p, 32);
        PROF(15 + l * 24);
        st.acquire();
        const int rr = 16 * w4 + (lane & 15), hi = lane >> 4, sw = (rr >> 1) & 3;
#pragma unroll
        for (int i = 0; i < 12; i += 2)
          stsm4(stg + (i >> 2) * 4096 + rr * 64 + ((((i & 3) + hi) ^ sw) << 4),
                pack2(bf_lo(z1a[i]) * (acc[4 * i] + bs0), bf_hi(z1a[i]) * (acc[4 * i + 1] + bs0)),
                pack2(bf_lo(z1b[i]) * (acc[4 * i + 2] + bs1), bf_hi(z1b[i]) * (acc[4 * i + 3] + bs1)),
                pack2(bf_lo(z1a[i + 1]) * (acc[4 * i + 4] + bs0), bf_hi(z1a[i + 1]) * (acc[4 * i + 5] + bs0)),
                pack2(bf_lo(z1b[i + 1]) * (acc[4 * i + 6] + bs1), bf_hi(z1b[i + 1]) * (acc[4 * i + 7] + bs1)));
        st.publish();
        PROF(16 + l * 24);
      }
      {
        float acc[40];
        gemm1<80>(acc, p, (hl & 1) ? 12 : 10);
        PROF(((hl & 1) ? 17 : 8) + l * 24);
        st.acquire();
        const uint32_t rowaddr = stg + (16 * w4 + (lane & 15)) * 160 + (lane >> 4) * 16;
        float s0 = 0.f, t0 = 0.f, s1 = 0.f, t1 = 0.f;
#pragma unroll
        for (int i = 0; i < 10; i += 2) {
          uint32_t x0, x1, x2, x3;
          asm volatile("ldmatrix.sync.aligned.m8n8.x4.shared.b16 {%0, %1, %2, %3}, [%4];" : "=r"(x0), "=r"(x1), "=r"(x2), "=r"(x3) : "r"(rowaddr + i * 16));
          x0 = pack2(acc[4 * i] + bf_lo(x0), acc[4 * i + 1] + bf_hi(x0));
          x1 = pack2(acc[4 * i + 2] + bf_lo(x1), acc[4 * i + 3] + bf_hi(x1));
          x2 = pack2(acc[4 * i + 4] + bf_lo(x2), acc[4 * i + 5] + bf_hi(x2));
          x3 = pack2(acc[4 * i + 6] + bf_lo(x3), acc[4 * i + 7] + bf_hi(x3));
          stsm4(rowaddr + i * 16, x0, x1, x2, x3);
          s0 += (bf_lo(x0) + bf_hi(x0)) + (bf_lo(x2) + bf_hi(x2)); s1 += (bf_lo(x1) + bf_hi(x1)) + (bf_lo(x3) + bf_hi(x3));
          t0 = fmaf(bf_lo(x0), bf_lo(x0), fmaf(bf_hi(x0), bf_hi(x0), fmaf(bf_lo(x2), bf_lo(x2), fmaf(bf_hi(x2), bf_hi(x2), t0))));
          t1 = fmaf(bf_lo(x1), bf_lo(x1), fmaf(bf_hi(x1), bf_hi(x1), fmaf(bf_lo(x3), bf_lo(x3), fmaf(bf_hi(x3), bf_hi(x3), t1))));
        }
#pragma unroll
        for (int m = 1; m <= 2; m <<= 1) {
          s0 += __shfl_xor_sync(0xffffffffu, s0, m); t0 += __shfl_xor_sync(0xffffffffu, t0, m);
          s1 += __shfl_xor_sync(0xffffffffu, s1, m); t1 += __shfl_xor_sync(0xffffffffu, t1, m);
        }
        if (q == 0) { sts64f(statS + rw * 8, s0, t0); sts64f(statS + (rw + 8) * 8, s1, t1); }
        st.publish();
        PROF(((hl & 1) ? 18 : 9) + l * 24);
      }
    }
    PROFG(64 + 61);
  }
}

typedef CUresult (*EncodeFn)(CUtensorMap*, CUtensorMapDataType, cuuint32_t, void*, const cuuint64_t*, const cuuint64_t*, const cuuint32_t*,
                             const cuuint32_t*, CUtensorMapInterleave, CUtensorMapSwizzle, CUtensorMapL2promotion, CUtensorMapFloatOOBfill);

CUtensorMap map2d(EncodeFn fn, const void* ptr, uint64_t rows, uint64_t cols, uint32_t box_rows, uint32_t box_cols, CUtensorMapSwizzle sw) {
  CUtensorMap m;
  cuuint64_t dims[2] = {cols, rows}, strides[1] = {cols * 2};
  cuuint32_t box[2] = {box_cols, box_rows}, es[2] = {1, 1};
  fn(&m, CU_TENSOR_MAP_DATA_TYPE_BFLOAT16, 2, const_cast<void*>(ptr), dims, strides, box, es, CU_TENSOR_MAP_INTERLEAVE_NONE, sw,
     CU_TENSOR_MAP_L2_PROMOTION_L2_256B, CU_TENSOR_MAP_FLOAT_OOB_FILL_NONE);
  return m;
}

}

extern "C" void kernel_launch(void* const* d_in, const int* in_sizes, int n_in, void* d_out, int out_size) {
  (void)in_sizes; (void)n_in; (void)out_size;
  static bool init = false;
  static Maps M;
  static Params P;
  static void* cached_ptrs[10];
  bool same = init;
  for (int i = 0; i < 9 && same; i++) same = cached_ptrs[i] == d_in[i];
  same = same && cached_ptrs[9] == d_out;
  if (!same) {
    void* fp = nullptr;
    cudaDriverEntryPointQueryResult st;
    cudaGetDriverEntryPoint("cuTensorMapEncodeTiled", &fp, cudaEnableDefault, &st);
    EncodeFn fn = (EncodeFn)fp;
    void *act, *h, *z, *wq, *wo, *wi, *wout;
    cudaGetSymbolAddress(&act, g_act); cudaGetSymbolAddress(&h, g_h); cudaGetSymbolAddress(&z, g_z);
    cudaGetSymbolAddress(&wq, g_Wq); cudaGetSymbolAddress(&wo, g_Wo); cudaGetSymbolAddress(&wi, g_Wi); cudaGetSymbolAddress(&wout, g_Wout);
    const CUtensorMapSwizzle S128 = CU_TENSOR_MAP_SWIZZLE_128B;
    M.x0 = map2d(fn, d_in[0], 2048, 640, 128, 64, S128);
    M.act = map2d(fn, act, 4 * 2048, 640, 128, 64, S128);
    M.wsp = map2d(fn, d_in[6], 2048, 2048, 128, 64, S128);
    M.h = map2d(fn, h, 2048, 768, 128, 64, S128);
    M.wq = map2d(fn, wq, 1920, 640, 80, 64, S128);
    M.wo = map2d(fn, wo, 640, 640, 80, 64, S128);
    M.wi = map2d(fn, wi, 1536, 640, 96, 64, S128);
    M.z = map2d(fn, z, 768, 2048, 96, 64, S128);
    M.wout = map2d(fn, wout, 640, 768, 80, 64, S128);
    M.sAct = map2d(fn, act, 4 * 2048, 640, 64, 80, CU_TENSOR_MAP_SWIZZLE_NONE);
    M.sOut = map2d(fn, d_out, 2048, 640, 64, 80, CU_TENSOR_MAP_SWIZZLE_NONE);
    M.sZ = map2d(fn, z, 768, 2048, 96, 64, S128);
    M.sWq = map2d(fn, wq, 1920, 640, 80, 32, CU_TENSOR_MAP_SWIZZLE_NONE);
    M.lWo = map2d(fn, d_in[3], 640, 640, 64, 32, CU_TENSOR_MAP_SWIZZLE_64B);
    M.lWi = map2d(fn, d_in[5], 640, 1536, 64, 32, CU_TENSOR_MAP_SWIZZLE_64B);
    M.lWout = map2d(fn, d_in[8], 768, 640, 64, 32, CU_TENSOR_MAP_SWIZZLE_64B);
    M.sWo = map2d(fn, wo, 640, 640, 32, 64, S128);
    M.sWi = map2d(fn, wi, 1536, 640, 32, 64, S128);
    M.sWout = map2d(fn, wout, 640, 768, 32, 64, S128);
    M.rX0 = map2d(fn, d_in[0], 2048, 640, 64, 80, CU_TENSOR_MAP_SWIZZLE_NONE);
    {
      cuuint64_t dims[3] = {32, 2048, 24}, strides[2] = {768 * 2, 64};
      cuuint32_t box[3] = {32, 64, 3}, es[3] = {1, 1, 1};
      fn(&M.sH, CU_TENSOR_MAP_DATA_TYPE_BFLOAT16, 3, h, dims, strides, box, es, CU_TENSOR_MAP_INTERLEAVE_NONE, CU_TENSOR_MAP_SWIZZLE_64B,
         CU_TENSOR_MAP_L2_PROMOTION_NONE, CU_TENSOR_MAP_FLOAT_OOB_FILL_NONE);
    }
    P.x = (const __nv_bfloat16*)d_in[0]; P.wqkv = (const __nv_bfloat16*)d_in[1]; P.wphi = (const __nv_bfloat16*)d_in[2];
    P.wo = (const __nv_bfloat16*)d_in[3]; P.win = (const __nv_bfloat16*)d_in[5]; P.wsp = (const __nv_bfloat16*)d_in[6];
    P.bsp = (const __nv_bfloat16*)d_in[7]; P.wout = (const __nv_bfloat16*)d_in[8];
    cudaFuncSetAttribute(mega_kernel, cudaFuncAttributeMaxDynamicSharedMemorySize, SMEM_BYTES);
    for (int i = 0; i < 9; i++) cached_ptrs[i] = d_in[i];
    cached_ptrs[9] = d_out;
    init = true;
  }
  mega_kernel<<<NCTA, NTHREADS, SMEM_BYTES>>>(M, P);
}
```

```cpp
#include <cuda_runtime.h>
#include <cuda_bf16.h>
#include <cuda.h>
#include <stdint.h>

namespace {

constexpr int S_ = 2048, D_ = 640, FH_ = 768;
constexpr int NCTA = 128;
constexpr int NTHREADS = 384;

constexpr int SA = 5, SB = 6;
constexpr int A_SLOT = 16384, B_SLOT = 12288;
constexpr int OFF_A = 0;
constexpr int OFF_B = OFF_A + SA * A_SLOT;
constexpr int OFF_STG = OFF_B + SB * B_SLOT;
constexpr int STG_WG = 33792;
constexpr int OFF_MISC = OFF_STG + 2 * STG_WG;
constexpr int OFF_BAR = OFF_MISC;
constexpr int BAR_STREADY = 22, BAR_STFREE = 24, BAR_XSTAT = 26, BAR_ZSTAT = 28, BAR_KV = 30, BAR_PRO = 31, BAR_TR = 32, BAR_TR2 = 33, BAR_IN = 34, BAR_XS = 35, BAR_KVL = 36, BAR_GO = 38, BAR_PUBA = 39, BAR_PUBB = 40;
constexpr int OFF_ABORT = OFF_MISC + 336;
constexpr int OFF_CSQ = OFF_MISC + 352;
constexpr int OFF_CSI = OFF_CSQ + 240 * 4;
constexpr int OFF_STAT = OFF_MISC + 2176;
constexpr int OFF_XRS = OFF_STAT + 1024;
constexpr int OFF_ZRS = OFF_XRS + 1024;
constexpr int SMEM_USED = OFF_ZRS + 1024;
constexpr int SMEM_BYTES = SMEM_USED + 1024;
constexpr int PRO_W = OFF_B;
constexpr int PRO_CS = PRO_W + 20480;
constexpr int PRO_ZERO = PRO_CS + 640;
constexpr int PRO_PHI = PRO_ZERO + 1920;
constexpr int PRO_IN = PRO_PHI + 8 * 1152;
constexpr int PRO_PITCH = 336;
constexpr int TR_IN = OFF_STG, TR_OUT = OFF_STG + 32768;
static_assert(PRO_IN + 64 * PRO_PITCH <= OFF_STG && PRO_PHI % 16 == 0 && PRO_IN % 16 == 0, "prologue staging");
static_assert(OFF_STG % 1024 == 0 && STG_WG % 1024 == 0, "staging alignment");
static_assert(OFF_CSI + 192 * 4 <= OFF_STAT, "misc overlap");
static_assert(SMEM_BYTES <= 232448, "smem budget");
constexpr int PHK_HS = 5 * 1024 + 32;
constexpr int VS_OFF = 4 * PHK_HS;
constexpr int VS_HS = 3 * 1024 + 32;
constexpr int PHQ_HS = 6 * 1024 + 32;
constexpr int KVS_OFF = 4 * PHQ_HS;
static_assert(VS_OFF + 4 * VS_HS <= STG_WG && KVS_OFF + 7680 <= STG_WG && KVS_OFF % 128 == 0, "staging layout");

__device__ __nv_bfloat16 g_Wq[1920 * 640];
__device__ float g_csq[2 * 1920];
__device__ __nv_bfloat16 g_Wo[640 * 640];
__device__ __nv_bfloat16 g_Wi[1536 * 640];
__device__ float g_csi[2 * 1536];
__device__ __nv_bfloat16 g_Wout[640 * 768];
__device__ __nv_bfloat16 g_act[4 * S_ * D_];
__device__ __nv_bfloat16 g_h[S_ * FH_];
__device__ __nv_bfloat16 g_z[FH_ * S_];
__device__ float2 g_xstat[4 * 16 * 8 * 128];
__device__ uint4 g_zstat[16 * 8 * 128];
__device__ float g_kv[2 * 2 * 8 * 3840];
constexpr int C_BGA = 1, C_BGB = 2;
constexpr int C_KV = 3;
constexpr int C_Z2 = C_KV + 16;
constexpr int C_O = C_Z2 + 16;
constexpr int C_X1 = C_O + 64;
constexpr int C_H = C_X1 + 64;
constexpr int C_X2 = C_H + 64;
constexpr int C_X0 = C_X2 + 32;
constexpr int C_W = C_X0 + 16;
constexpr int C_NUM = C_W + 120;
__device__ unsigned g_cnt[C_NUM * 32];
__device__ unsigned g_epoch;
#define PROF(i)
#define PROFW(i)
#define PROFG(i)
#define PROF_ST_IF(i)
#define PROF_DECL

struct Maps {
  CUtensorMap x0, act, wsp, h, wq, wo, wi, z, wout;
  CUtensorMap lWo, lWi, lWout;
  CUtensorMap rX0;
  CUtensorMap sAct, sOut, sH, sZ, sWo, sWi, sWout;
};

__device__ __forceinline__ uint32_t smem_u32(const void* p) { return (uint32_t)__cvta_generic_to_shared(p); }
__device__ __forceinline__ uint32_t uniform(uint32_t x) {
  uint32_t y; asm volatile("mov.u32 %0, %1;" : "=r"(y) : "r"(x)); return __shfl_sync(0xffffffffu, y, 0);
}
__device__ __forceinline__ uint32_t opaque(uint32_t x) { uint32_t y; asm volatile("mov.u32 %0, %1;" : "=r"(y) : "r"(x)); return y; }
__device__ __forceinline__ bool elect_one() {
  uint32_t p; asm volatile("{ .reg .pred P; elect.sync _|P, 0xffffffff; selp.u32 %0, 1, 0, P; }" : "=r"(p)); return p;
}
__device__ __forceinline__ void mbar_init(uint32_t bar, uint32_t cnt) { asm volatile("mbarrier.init.shared::cta.b64 [%0], %1;" :: "r"(bar), "r"(cnt) : "memory"); }
__device__ __forceinline__ void mbar_expect_tx(uint32_t bar, uint32_t bytes) { asm volatile("mbarrier.arrive.expect_tx.shared::cta.b64 _, [%0], %1;" :: "r"(bar), "r"(bytes) : "memory"); }
__device__ __forceinline__ void mbar_arrive(uint32_t bar) { asm volatile("mbarrier.arrive.shared::cta.b64 _, [%0];" :: "r"(bar) : "memory"); }
__device__ __forceinline__ bool mbar_try(uint32_t bar, uint32_t parity) {
  uint32_t ok;
  asm volatile("{ .reg .pred p; mbarrier.try_wait.parity.shared::cta.b64 p, [%1], %2; selp.u32 %0, 1, 0, p; }" : "=r"(ok) : "r"(bar), "r"(parity) : "memory");
  return ok;
}
__device__ __forceinline__ uint32_t lds32v(uint32_t a) { uint32_t v; asm volatile("ld.volatile.shared.u32 %0, [%1];" : "=r"(v) : "r"(a) : "memory"); return v; }
__device__ __forceinline__ void mbar_wait(uint32_t bar, uint32_t parity, uint32_t abort_addr) {
  if (__builtin_expect(!mbar_try(bar, parity), 0)) {
    uint32_t n = 0;
#pragma unroll 1
    while (!mbar_try(bar, parity)) {
      if (lds32v(abort_addr) != 0) break;
      if (++n > (1u << 20)) { asm volatile("st.volatile.shared.u32 [%0], 1;" :: "r"(abort_addr) : "memory"); break; }
    }
  }
}
__device__ __forceinline__ void tma_load(uint32_t dst, const CUtensorMap* map, int c0, int c1, uint32_t bar) {
  asm volatile("cp.async.bulk.tensor.2d.shared::cluster.global.mbarrier::complete_tx::bytes [%0], [%1, {%3, %4}], [%2];"
               :: "r"(dst), "l"(map), "r"(bar), "r"(c0), "r"(c1) : "memory");
}
__device__ __forceinline__ void tma_store2(const CUtensorMap* map, uint32_t src, int c0, int c1) {
  asm volatile("cp.async.bulk.tensor.2d.global.shared::cta.bulk_group [%0, {%2, %3}], [%1];" :: "l"(map), "r"(src), "r"(c0), "r"(c1) : "memory");
}
__device__ __forceinline__ void tma_store3(const CUtensorMap* map, uint32_t src, int c0, int c1, int c2) {
  asm volatile("cp.async.bulk.tensor.3d.global.shared::cta.bulk_group [%0, {%2, %3, %4}], [%1];" :: "l"(map), "r"(src), "r"(c0), "r"(c1), "r"(c2) : "memory");
}
__device__ __forceinline__ void bulk_store(void* dst, uint32_t src, uint32_t bytes) {
  asm volatile("cp.async.bulk.global.shared::cta.bulk_group [%0], [%1], %2;" :: "l"(dst), "r"(src), "r"(bytes) : "memory");
}
__device__ __forceinline__ void bulk_reduce_add_f32(void* dst, uint32_t src, uint32_t bytes) {
  asm volatile("cp.reduce.async.bulk.global.shared::cta.bulk_group.add.f32 [%0], [%1], %2;" :: "l"(dst), "r"(src), "r"(bytes) : "memory");
}
__device__ __forceinline__ void bulk_commit_wait() {
  asm volatile("cp.async.bulk.commit_group;" ::: "memory");
  asm volatile("cp.async.bulk.wait_group 0;" ::: "memory");
}
__device__ __forceinline__ void fence_async_smem() { asm volatile("fence.proxy.async.shared::cta;" ::: "memory"); }
__device__ __forceinline__ void fence_async_global() { asm volatile("fence.proxy.async.global;" ::: "memory"); }
__device__ __forceinline__ void bar_sync(int id, int n) { asm volatile("bar.sync %0, %1;" :: "r"(id), "r"(n) : "memory"); }
#define MK_FENCE_MASK 0xff
__device__ __forceinline__ void cnt_add(int idx, int kind, unsigned n = 1) {
  if ((MK_FENCE_MASK >> kind) & 1) {
    asm volatile("fence.proxy.async.global;" ::: "memory");
    asm volatile("red.release.gpu.global.add.u32 [%0], %1;" :: "l"(&g_cnt[idx * 32]), "r"(n) : "memory");
  } else {
    asm volatile("red.relaxed.gpu.global.add.u32 [%0], %1;" :: "l"(&g_cnt[idx * 32]), "r"(n) : "memory");
  }
}
__device__ __forceinline__ void cnt_wait(int idx, unsigned target, uint32_t abort_addr) {
  asm volatile("{\n .reg .pred p;\n .reg .u32 n, v, a;\n mov.u32 n, 0;\n"
               "LAB_WAIT:\n ld.relaxed.gpu.global.u32 v, [%0];\n sub.u32 v, v, %1;\n setp.ge.s32 p, v, 0;\n @p bra LAB_DONE;\n"
               " ld.volatile.shared.u32 a, [%2];\n setp.ne.u32 p, a, 0;\n @p bra LAB_DONE;\n"
               " add.u32 n, n, 1;\n setp.lt.u32 p, n, 1048576;\n @p bra LAB_WAIT;\n"
               " st.volatile.shared.u32 [%2], 1;\n LAB_DONE:\n }"
               :: "l"(&g_cnt[idx * 32]), "r"(target), "r"(abort_addr) : "memory");
}
__device__ __forceinline__ void cnt_wait_warp(int idx, unsigned target, uint32_t abort_addr) {
  if ((threadIdx.x & 31) == 0) cnt_wait(idx, target, abort_addr);
  __syncwarp();
}
__device__ __forceinline__ uint64_t make_desc(uint32_t saddr, uint32_t lbo, uint32_t sbo, uint64_t layout) {
  return (uint64_t)((saddr & 0x3FFFF) >> 4) | ((uint64_t)(lbo >> 4) << 16) | ((uint64_t)(sbo >> 4) << 32) | (layout << 62);
}
__device__ __forceinline__ void wg_fence() { asm volatile("wgmma.fence.sync.aligned;" ::: "memory"); }
__device__ __forceinline__ void wg_commit() { asm volatile("wgmma.commit_group.sync.aligned;" ::: "memory"); }
template <int N> __device__ __forceinline__ void wg_wait() { asm volatile("wgmma.wait_group.sync.aligned %0;" :: "n"(N) : "memory"); }
template <int N> __device__ __forceinline__ void fresh(float (&a)[N]) {
#pragma unroll
  for (int i = 0; i < N; i++) asm volatile("mov.b32 %0, 0;" : "=f"(a[i]));
}
template <int N> __device__ __forceinline__ void pin(float (&a)[N]) {
#pragma unroll
  for (int i = 0; i < N; i++) asm volatile("" : "+f"(a[i]) :: "memory");
}
__device__ __forceinline__ uint32_t pack2(float lo, float hi) {
  uint32_t r; asm("cvt.rn.bf16x2.f32 %0, %1, %2;" : "=r"(r) : "f"(hi), "f"(lo)); return r;
}
__device__ __forceinline__ float bf_lo(uint32_t v) { return __uint_as_float(v << 16); }
__device__ __forceinline__ float bf_hi(uint32_t v) { return __uint_as_float(v & 0xffff0000u); }
__device__ __forceinline__ float ex2(float x) { float y; asm("ex2.approx.ftz.f32 %0, %1;" : "=f"(y) : "f"(x)); return y; }
__device__ __forceinline__ float rcp(float x) { float y; asm("rcp.approx.ftz.f32 %0, %1;" : "=f"(y) : "f"(x)); return y; }
__device__ __forceinline__ void sts128(uint32_t a, uint32_t x, uint32_t y, uint32_t z, uint32_t w) {
  asm volatile("st.shared.v4.u32 [%0], {%1, %2, %3, %4};" :: "r"(a), "r"(x), "r"(y), "r"(z), "r"(w) : "memory");
}
__device__ __forceinline__ void sts32(uint32_t a, uint32_t x) { asm volatile("st.shared.u32 [%0], %1;" :: "r"(a), "r"(x) : "memory"); }
__device__ __forceinline__ void sts64f(uint32_t a, float x, float y) { asm volatile("st.shared.v2.f32 [%0], {%1, %2};" :: "r"(a), "f"(x), "f"(y) : "memory"); }
__device__ __forceinline__ float2 lds64f(uint32_t a) { float2 v; asm volatile("ld.shared.v2.f32 {%0, %1}, [%2];" : "=f"(v.x), "=f"(v.y) : "r"(a)); return v; }
__device__ __forceinline__ void stsm4(uint32_t a, uint32_t r0, uint32_t r1, uint32_t r2, uint32_t r3) {
  asm volatile("stmatrix.sync.aligned.m8n8.x4.shared.b16 [%0], {%1, %2, %3, %4};" :: "r"(a), "r"(r0), "r"(r1), "r"(r2), "r"(r3) : "memory");
}
__device__ __forceinline__ void stsm4t(uint32_t a, uint32_t r0, uint32_t r1, uint32_t r2, uint32_t r3) {
  asm volatile("stmatrix.sync.aligned.m8n8.x4.trans.shared.b16 [%0], {%1, %2, %3, %4};" :: "r"(a), "r"(r0), "r"(r1), "r"(r2), "r"(r3) : "memory");
}
__device__ __forceinline__ void mma16816(float (&c)[4], const uint32_t (&a)[4], uint32_t b0, uint32_t b1) {
  asm volatile("mma.sync.aligned.m16n8k16.row.col.f32.bf16.bf16.f32 {%0, %1, %2, %3}, {%4, %5, %6, %7}, {%8, %9}, {%0, %1, %2, %3};"
               : "+f"(c[0]), "+f"(c[1]), "+f"(c[2]), "+f"(c[3]) : "r"(a[0]), "r"(a[1]), "r"(a[2]), "r"(a[3]), "r"(b0), "r"(b1));
}

template <int TA, int TB>
__device__ __forceinline__ void wgmma_n24(float (&d)[12], uint64_t da, uint64_t db, int scale_d) {
  asm volatile("{ .reg .pred p; setp.ne.b32 p, %14, 0; "
    "wgmma.mma_async.sync.aligned.m64n24k16.f32.bf16.bf16 "
    "{%0, %1, %2, %3, %4, %5, %6, %7, %8, %9, %10, %11}, "
    "%12, %13, p, 1, 1, %15, %16; }"
    : "+f"(d[0]), "+f"(d[1]), "+f"(d[2]), "+f"(d[3]), "+f"(d[4]), "+f"(d[5]), "+f"(d[6]), "+f"(d[7]), "+f"(d[8]), "+f"(d[9]), "+f"(d[10]), "+f"(d[11])
    : "l"(da), "l"(db), "r"(scale_d), "n"(TA), "n"(TB));
}
template <int TA, int TB>
__device__ __forceinline__ void wgmma_n80(float (&d)[40], uint64_t da, uint64_t db, int scale_d) {
  asm volatile("{ .reg .pred p; setp.ne.b32 p, %42, 0; "
    "wgmma.mma_async.sync.aligned.m64n80k16.f32.bf16.bf16 "
    "{%0, %1, %2, %3, %4, %5, %6, %7, %8, %9, %10, %11, %12, %13, %14, %15, %16, %17, %18, %19, %20, %21, %22, %23, %24, %25, %26, %27, %28, %29, %30, %31, %32, %33, %34, %35, %36, %37, %38, %39}, "
    "%40, %41, p, 1, 1, %43, %44; }"
    : "+f"(d[0]), "+f"(d[1]), "+f"(d[2]), "+f"(d[3]), "+f"(d[4]), "+f"(d[5]), "+f"(d[6]), "+f"(d[7]), "+f"(d[8]), "+f"(d[9]), "+f"(d[10]), "+f"(d[11]), "+f"(d[12]), "+f"(d[13]), "+f"(d[14]), "+f"(d[15]), "+f"(d[16]), "+f"(d[17]), "+f"(d[18]), "+f"(d[19]), "+f"(d[20]), "+f"(d[21]), "+f"(d[22]), "+f"(d[23]), "+f"(d[24]), "+f"(d[25]), "+f"(d[26]), "+f"(d[27]), "+f"(d[28]), "+f"(d[29]), "+f"(d[30]), "+f"(d[31]), "+f"(d[32]), "+f"(d[33]), "+f"(d[34]), "+f"(d[35]), "+f"(d[36]), "+f"(d[37]), "+f"(d[38]), "+f"(d[39])
    : "l"(da), "l"(db), "r"(scale_d), "n"(TA), "n"(TB));
}
template <int TA, int TB>
__device__ __forceinline__ void wgmma_n96(float (&d)[48], uint64_t da, uint64_t db, int scale_d) {
  asm volatile("{ .reg .pred p; setp.ne.b32 p, %50, 0; "
    "wgmma.mma_async.sync.aligned.m64n96k16.f32.bf16.bf16 "
    "{%0, %1, %2, %3, %4, %5, %6, %7, %8, %9, %10, %11, %12, %13, %14, %15, %16, %17, %18, %19, %20, %21, %22, %23, %24, %25, %26, %27, %28, %29, %30, %31, %32, %33, %34, %35, %36, %37, %38, %39, %40, %41, %42, %43, %44, %45, %46, %47}, "
    "%48, %49, p, 1, 1, %51, %52; }"
    : "+f"(d[0]), "+f"(d[1]), "+f"(d[2]), "+f"(d[3]), "+f"(d[4]), "+f"(d[5]), "+f"(d[6]), "+f"(d[7]), "+f"(d[8]), "+f"(d[9]), "+f"(d[10]), "+f"(d[11]), "+f"(d[12]), "+f"(d[13]), "+f"(d[14]), "+f"(d[15]), "+f"(d[16]), "+f"(d[17]), "+f"(d[18]), "+f"(d[19]), "+f"(d[20]), "+f"(d[21]), "+f"(d[22]), "+f"(d[23]), "+f"(d[24]), "+f"(d[25]), "+f"(d[26]), "+f"(d[27]), "+f"(d[28]), "+f"(d[29]), "+f"(d[30]), "+f"(d[31]), "+f"(d[32]), "+f"(d[33]), "+f"(d[34]), "+f"(d[35]), "+f"(d[36]), "+f"(d[37]), "+f"(d[38]), "+f"(d[39]), "+f"(d[40]), "+f"(d[41]), "+f"(d[42]), "+f"(d[43]), "+f"(d[44]), "+f"(d[45]), "+f"(d[46]), "+f"(d[47])
    : "l"(da), "l"(db), "r"(scale_d), "n"(TA), "n"(TB));
}

template <int N, int TA, int TB>
__device__ __forceinline__ void wgmma(float (&d)[N / 2], uint64_t da, uint64_t db, int s) {
  if constexpr (N == 24) wgmma_n24<TA, TB>(d, da, db, s);
  else if constexpr (N == 80) wgmma_n80<TA, TB>(d, da, db, s);
  else wgmma_n96<TA, TB>(d, da, db, s);
}

struct Pipe {
  uint32_t fullA, emptyA, fullB, emptyB, ab;
  uint64_t dA, dB;
  int sa, sb;
  uint32_t pa, pb;
  bool leader;
  __device__ __forceinline__ void advA() { if (++sa == SA) { sa = 0; pa ^= 1; } }
  __device__ __forceinline__ void advB() { if (++sb == SB) { sb = 0; pb ^= 1; } }
};

template <int N, bool CONT = false>
__device__ __forceinline__ void gemm1(float (&acc)[N / 2], Pipe& p, int NK) {
  int ra = 0, rb = 0;
  if (!CONT) fresh(acc);
#pragma unroll 1
  for (int kb = 0; kb < NK; kb++) {
    mbar_wait(p.fullB + p.sb * 8, p.pb, p.ab);
    mbar_wait(p.fullA + p.sa * 8, p.pa, p.ab);
    wg_fence();
    const uint64_t da = p.dA + (uint64_t)(p.sa * (A_SLOT >> 4)), db = p.dB + (uint64_t)(p.sb * (B_SLOT >> 4));
#pragma unroll
    for (int k = 0; k < 4; k++) wgmma<N, 0, 0>(acc, da + k * 2, db + k * 2, (CONT || kb > 0 || k > 0) ? 1 : 0);
    wg_commit();
    wg_wait<1>();
    if (kb > 0 && p.leader) { mbar_arrive(p.emptyA + ra * 8); mbar_arrive(p.emptyB + rb * 8); }
    ra = p.sa; rb = p.sb;
    p.advA(); p.advB();
  }
  wg_wait<0>();
  pin(acc);
  if (p.leader) { mbar_arrive(p.emptyA + ra * 8); mbar_arrive(p.emptyB + rb * 8); }
}
__device__ __forceinline__ void feature_rows(float (&acc)[40], uint32_t cs_addr, float m0, float r0, float m1, float r1, uint32_t addr, bool pad) {
  constexpr float LOG2E = 1.4426950408889634f;
  float nm = -m0, a = r0 * LOG2E;
#pragma unroll 1
  for (int h = 0; h < 2; h++) {
    float u[20];
#pragma unroll
    for (int i = 0; i < 10; i++) {
      const float2 c = lds64f(cs_addr + i * 32);
      u[2 * i] = fmaf(nm, c.x, acc[4 * i]); u[2 * i + 1] = fmaf(nm, c.y, acc[4 * i + 1]);
      acc[4 * i] = acc[4 * i + 2]; acc[4 * i + 1] = acc[4 * i + 3];
    }
    float mx[2], mn[2];
#pragma unroll
    for (int k = 0; k < 2; k++) { mx[k] = fmaxf(u[k], u[k + 2]); mn[k] = fminf(u[k], u[k + 2]); }
#pragma unroll
    for (int f = 4; f < 20; f++) { mx[f & 1] = fmaxf(mx[f & 1], u[f]); mn[f & 1] = fminf(mn[f & 1], u[f]); }
    const float bp = -a * fmaxf(mx[0], mx[1]), bn = a * fminf(mn[0], mn[1]);
    float ep[20], en[20], sp[2], sn[2];
#pragma unroll
    for (int f = 0; f < 20; f++) {
      ep[f] = ex2(fmaf(u[f], a, bp));
      en[f] = ex2(fmaf(u[f], -a, bn));
      if (f < 2) { sp[f] = ep[f]; sn[f] = en[f]; } else { sp[f & 1] += ep[f]; sn[f & 1] += en[f]; }
    }
    const float rp = rcp(sp[0] + sp[1]), rn = rcp(sn[0] + sn[1]);
    uint32_t w[20];
#pragma unroll
    for (int f = 0; f < 10; f++) { w[f] = pack2(ep[2 * f] * rp, ep[2 * f + 1] * rp); w[10 + f] = pack2(en[2 * f] * rn, en[2 * f + 1] * rn); }
#pragma unroll
    for (int c = 0; c < 5; c++) sts128(addr + c * 1024, w[4 * c], w[4 * c + 1], w[4 * c + 2], w[4 * c + 3]);
    if (pad) sts128(addr + 5 * 1024, 0u, 0u, 0u, 0u);
    addr += 128; nm = -m1; a = r1 * LOG2E;
  }
}

struct GeluRow {
  float nm, A, B, H;
  __device__ __forceinline__ GeluRow(float m, float rs) : nm(-m), A(0.7978845608029f * rs), B(0.0356774081363f * rs * rs * rs), H(0.5f * rs) {}
  __device__ __forceinline__ float operator()(float acc, float c) const {
    const float y = fmaf(nm, c, acc);
    const float u = y * fmaf(y * y, B, A), hx = H * y;
    float t;
    asm("tanh.approx.f32 %0, %1;" : "=f"(t) : "f"(u));
    return fmaf(hx, t, hx);
  }
};
template <bool STATS>
__device__ __forceinline__ void gelu_rows(const float (&acc)[48], uint32_t cs_addr, float m0, float r0, float m1, float r1,
                                          uint32_t (&za)[12], uint32_t (&zb)[12], uint4* stat_dst, uint32_t tag, bool stat_lane) {
  const GeluRow g0(m0, r0), g1(m1, r1);
  float s0 = 0.f, t0 = 0.f, s1 = 0.f, t1 = 0.f;
#pragma unroll
  for (int i = 0; i < 12; i++) {
    const float2 c = lds64f(cs_addr + i * 32);
    za[i] = pack2(g0(acc[4 * i], c.x), g0(acc[4 * i + 1], c.y));
    zb[i] = pack2(g1(acc[4 * i + 2], c.x), g1(acc[4 * i + 3], c.y));
    if (STATS) {
      const float x = bf_lo(za[i]), y = bf_hi(za[i]), z = bf_lo(zb[i]), w = bf_hi(zb[i]);
      s0 += x + y; t0 = fmaf(x, x, fmaf(y, y, t0)); s1 += z + w; t1 = fmaf(z, z, fmaf(w, w, t1));
    }
  }
  if (STATS) {
#pragma unroll
    for (int m = 1; m <= 2; m <<= 1) {
      s0 += __shfl_xor_sync(0xffffffffu, s0, m); t0 += __shfl_xor_sync(0xffffffffu, t0, m);
      s1 += __shfl_xor_sync(0xffffffffu, s1, m); t1 += __shfl_xor_sync(0xffffffffu, t1, m);
    }
    if (stat_lane) {
      asm volatile("st.relaxed.gpu.global.v2.b64 [%0], {%1, %2};" :: "l"(stat_dst), "l"(((uint64_t)tag << 32) | __float_as_uint(s0)), "l"(((uint64_t)tag << 32) | __float_as_uint(t0)) : "memory");
      asm volatile("st.relaxed.gpu.global.v2.b64 [%0], {%1, %2};" :: "l"(stat_dst + 8), "l"(((uint64_t)tag << 32) | __float_as_uint(s1)), "l"(((uint64_t)tag << 32) | __float_as_uint(t1)) : "memory");
    }
  }
}

struct Stage {
  uint32_t ready, freeb, ab, ph;
  __device__ __forceinline__ void acquire() { mbar_wait(freeb, ph, ab); ph ^= 1; }
  __device__ __forceinline__ void publish() {
    fence_async_smem();
    __syncwarp();
    if ((threadIdx.x & 31) == 0) mbar_arrive(ready);
  }
};

struct Params {
  const __nv_bfloat16 *x, *wqkv, *wphi, *wo, *win, *wsp, *bsp, *wout;
};

__device__ __forceinline__ void cp16(uint32_t dst, const void* src) { asm volatile("cp.async.cg.shared.global [%0], [%1], 16;" :: "r"(dst), "l"(src) : "memory"); }
__device__ __forceinline__ uint32_t lds32(uint32_t a) { uint32_t v; asm volatile("ld.shared.u32 %0, [%1];" : "=r"(v) : "r"(a)); return v; }

struct TrUnit { int which, k0, n0, drow; };
__device__ __forceinline__ TrUnit tr_unit(int u) {
  TrUnit t;
  t.which = u < 200 ? 0 : u < 680 ? 1 : 2;
  const int v = u - (t.which == 0 ? 0 : t.which == 1 ? 200 : 680), nk = t.which == 2 ? 12 : 10;
  t.k0 = 64 * (v % nk); t.n0 = 32 * (v / nk);
  const int m = t.n0 < 768 ? t.n0 : t.n0 - 768;
  t.drow = t.which == 1 ? 192 * (m / 96) + (t.n0 < 768 ? 96 : 0) + m % 96 : t.n0;
  return t;
}

__device__ __forceinline__ void prologue_loads(const Params& P, int b, uint32_t sb) {
  const int t256 = threadIdx.x;
  const bool fold = b < 120;
  const int kr = b % 10, cg = b / 10, t = cg >> 2, hb = 8 * (cg & 3);
  if (fold) {
#pragma unroll
    for (int i = 0; i < 5; i++) {
      const int c = t256 + 256 * i, row = c / 20, ch = c % 20;
      cp16(sb + PRO_IN + row * PRO_PITCH + ch * 16, P.wqkv + (size_t)(64 * kr + row) * 1920 + 640 * t + 20 * hb + 8 * ch);
    }
    if (t < 2) {
#pragma unroll 1
      for (int c = t256; c < 800; c += 256) {
        const int row = c / 5, pc = c % 5, h = row / 20, d = row % 20;
        asm volatile("cp.async.ca.shared.global [%0], [%1], 8;" :: "r"(sb + PRO_PHI + h * 1152 + d * 48 + pc * 8), "l"(P.wphi + (size_t)hb * 400 + c * 4) : "memory");
      }
      if (t256 < 96) sts128(sb + PRO_PHI + (t256 / 12) * 1152 + 960 + (t256 % 12) * 16, 0u, 0u, 0u, 0u);
    }
  }
  asm volatile("cp.async.commit_group;" ::: "memory");
}

__device__ __forceinline__ void prologue(const Params& P, int b, int r, int j, uint32_t sb, int warp, int lane) {
  PROF_DECL;
  const int g = lane >> 2, q = lane & 3, t256 = threadIdx.x;
  const bool fold = b < 120;
  const int t = (b / 10) >> 2;
  if (t256 < 120) sts128(sb + PRO_ZERO + t256 * 16, 0u, 0u, 0u, 0u);
  asm volatile("cp.async.wait_group 0;" ::: "memory");
  if (lane == 0) mbar_arrive(sb + OFF_BAR + BAR_IN * 8);
  PROF(64 + 56);
  bar_sync(3, 256);
  PROF(64 + 50);
  if (fold) {
    const int d0 = 2 * q;
    uint32_t a0[2][4], a1[2][4];
    if (t < 2) {
      const uint32_t ph = sb + PRO_PHI + warp * 1152, r8 = lane & 7, m = lane >> 3;
      asm volatile("ldmatrix.sync.aligned.m8n8.x4.trans.shared.b16 {%0, %1, %2, %3}, [%4];" : "=r"(a0[0][0]), "=r"(a0[0][1]), "=r"(a0[0][2]), "=r"(a0[0][3])
                   : "r"(ph + (8 * (m >> 1) + r8) * 48 + (m & 1) * 16));
      asm volatile("ldmatrix.sync.aligned.m8n8.x4.trans.shared.b16 {%0, %1, %2, %3}, [%4];" : "=r"(a1[0][0]), "=r"(a1[0][1]), "=r"(a0[1][0]), "=r"(a0[1][2])
                   : "r"(ph + (m < 2 ? (16 + r8) * 48 + m * 16 : (8 * (m - 2) + r8) * 48 + 32)));
      asm volatile("ldmatrix.sync.aligned.m8n8.x1.trans.shared.b16 {%0}, [%1];" : "=r"(a1[1][0]) : "r"(ph + (16 + r8) * 48 + 32));
    } else {
      auto one = [&](int f, int d) -> uint32_t { return (f == d ? 0x3f80u : 0u) | (f == d + 1 ? 0x3f800000u : 0u); };
      a0[0][0] = one(g, d0); a0[0][1] = one(g + 8, d0); a0[0][2] = one(g, d0 + 8); a0[0][3] = one(g + 8, d0 + 8);
      a1[0][0] = 0u; a1[0][1] = 0u; a0[1][0] = 0u; a0[1][2] = 0u; a1[1][0] = q < 2 ? one(g + 16, d0 + 16) : 0u;
    }
    a1[0][2] = a1[0][3] = 0u; a0[1][1] = a0[1][3] = 0u; a1[1][1] = a1[1][2] = a1[1][3] = 0u;
    const int n0 = 80 * (warp >> 2) + 8 * (g >> 1) + 2 * (warp & 3) + (g & 1);
    const uint32_t wrow = sb + PRO_W + n0 * 128 + q * 4;
    float cs[3] = {0.f, 0.f, 0.f};
#pragma unroll
    for (int half = 0; half < 2; half++) {
      uint32_t bw[4][3];
      float c[2][4][4];
#pragma unroll
      for (int nt = 0; nt < 4; nt++) {
        const uint32_t pw = sb + PRO_IN + (32 * half + 8 * nt + g) * PRO_PITCH + (20 * warp + 2 * q) * 2;
        bw[nt][0] = lds32(pw); bw[nt][1] = lds32(pw + 16); bw[nt][2] = q < 2 ? lds32(pw + 32) : 0u;
      }
#pragma unroll
      for (int mt = 0; mt < 2; mt++)
#pragma unroll
        for (int nt = 0; nt < 4; nt++) {
          c[mt][nt][0] = c[mt][nt][1] = c[mt][nt][2] = c[mt][nt][3] = 0.f;
          mma16816(c[mt][nt], a0[mt], bw[nt][0], bw[nt][1]);
        }
#pragma unroll
      for (int mt = 0; mt < 2; mt++)
#pragma unroll
        for (int nt = 0; nt < 4; nt++) mma16816(c[mt][nt], a1[mt], bw[nt][2], 0u);
#pragma unroll
      for (int nt = 0; nt < 4; nt++) {
        const uint32_t w0 = pack2(c[0][nt][0], c[0][nt][1]), w1 = pack2(c[0][nt][2], c[0][nt][3]), w2 = pack2(c[1][nt][0], c[1][nt][1]);
        cs[0] += bf_lo(w0) + bf_hi(w0); cs[1] += bf_lo(w1) + bf_hi(w1); cs[2] += bf_lo(w2) + bf_hi(w2);
        const uint32_t a = wrow + (((4 * half + nt) ^ (n0 & 7)) << 4);
        sts32(a, w0); sts32(a + 32 * 128, w1);
        if (g < 4) sts32(a + 64 * 128, w2);
      }
    }
#pragma unroll
    for (int k = 0; k < 3; k++) { cs[k] += __shfl_xor_sync(0xffffffffu, cs[k], 1); cs[k] += __shfl_xor_sync(0xffffffffu, cs[k], 2); }
    if (q == 0) {
      sts32(sb + PRO_CS + n0 * 4, __float_as_uint(cs[0])); sts32(sb + PRO_CS + (n0 + 32) * 4, __float_as_uint(cs[1]));
      if (g < 4) sts32(sb + PRO_CS + (n0 + 64) * 4, __float_as_uint(cs[2]));
    }
  }
  fence_async_smem();
  __syncwarp();
  if (lane == 0) mbar_arrive(sb + OFF_BAR + BAR_PRO * 8);
  PROF(64 + 52);
#pragma unroll
  for (int i = 0; i < 5; i++) {
    const int c = t256 + 256 * i, row = c / 10, ch = c % 10;
    cp16(sb + TR_OUT + c * 16, P.x + (size_t)(128 * r + row) * D_ + 80 * j + 8 * ch);
  }
  asm volatile("cp.async.commit_group;" ::: "memory");
  asm volatile("cp.async.wait_group 0;" ::: "memory");
  bar_sync(3, 256);
  {
    float s = 0.f, tt = 0.f;
#pragma unroll
    for (int i = 0; i < 5; i++) {
      uint32_t w[4];
      asm volatile("ld.shared.v4.u32 {%0, %1, %2, %3}, [%4];" : "=r"(w[0]), "=r"(w[1]), "=r"(w[2]), "=r"(w[3]) : "r"(sb + TR_OUT + t256 * 80 + i * 16));
#pragma unroll
      for (int c = 0; c < 4; c++) { const float a = bf_lo(w[c]), bb = bf_hi(w[c]); s += a + bb; tt = fmaf(a, a, fmaf(bb, bb, tt)); }
    }
    s += __shfl_xor_sync(0xffffffffu, s, 1); tt += __shfl_xor_sync(0xffffffffu, tt, 1);
    if ((t256 & 1) == 0) sts64f(sb + OFF_XRS + (t256 >> 1) * 8, s, tt);
    fence_async_smem();
    __syncwarp();
    if (lane == 0) mbar_arrive(sb + OFF_BAR + BAR_XS * 8);
  }
  bar_sync(3, 256);
  if (b + 128 * warp < 920) {
    const int m = lane >> 3, row = lane & 7;
    float cs[4] = {0.f, 0.f, 0.f, 0.f};
    mbar_wait(sb + OFF_BAR + BAR_TR * 8, 0, sb + OFF_ABORT);
#pragma unroll
    for (int a = 0; a < 8; a++) {
      uint32_t r0, r1, r2, r3;
      asm volatile("ldmatrix.sync.aligned.m8n8.x4.trans.shared.b16 {%0, %1, %2, %3}, [%4];" : "=r"(r0), "=r"(r1), "=r"(r2), "=r"(r3)
                   : "r"(sb + TR_IN + warp * 4096 + (8 * a + row) * 64 + ((m ^ ((row >> 1) & 3)) << 4)));
      stsm4(sb + TR_OUT + warp * 4096 + (8 * m + row) * 128 + ((a ^ row) << 4), r0, r1, r2, r3);
      cs[0] += bf_lo(r0) + bf_hi(r0); cs[1] += bf_lo(r1) + bf_hi(r1); cs[2] += bf_lo(r2) + bf_hi(r2); cs[3] += bf_lo(r3) + bf_hi(r3);
    }
#pragma unroll
    for (int c = 0; c < 4; c++) {
      cs[c] += __shfl_xor_sync(0xffffffffu, cs[c], 1); cs[c] += __shfl_xor_sync(0xffffffffu, cs[c], 2);
      if (q == 0) sts32(sb + OFF_ZRS + warp * 128 + (8 * c + g) * 4, __float_as_uint(cs[c]));
    }
    fence_async_smem();
  }
  __syncwarp();
  if (lane == 0) mbar_arrive(sb + OFF_BAR + BAR_TR2 * 8);
}

__global__ void __launch_bounds__(NTHREADS, 1) mega_kernel(const __grid_constant__ Maps M, const Params P) {
  extern __shared__ uint8_t smem_raw[];
  const uint32_t sb = uniform((smem_u32(smem_raw) + 1023) & ~1023u);
  const int warp = uniform(threadIdx.x >> 5), lane = threadIdx.x & 31;
  const int b = uniform(blockIdx.x), r = b >> 3, j = b & 7;
  const uint32_t bars = sb + OFF_BAR;
  const uint32_t fullA = bars, emptyA = fullA + SA * 8, fullB = emptyA + SA * 8, emptyB = fullB + SB * 8;
  const uint32_t ab = sb + OFF_ABORT;
  PROF_DECL;
  PROF(0);
  PROFG(64 + 60);
  if (warp < 8) prologue_loads(P, b, sb);
  if (threadIdx.x == 256) {
    asm volatile("st.shared.u32 [%0], 0;" :: "r"(ab) : "memory");
    for (int s = 0; s < SA; s++) { mbar_init(fullA + s * 8, 1); mbar_init(emptyA + s * 8, 2); }
    for (int s = 0; s < SB; s++) { mbar_init(fullB + s * 8, 1); mbar_init(emptyB + s * 8, 2); }
    for (int w = 0; w < 2; w++) {
      mbar_init(bars + (BAR_STREADY + w) * 8, 4); mbar_init(bars + (BAR_STFREE + w) * 8, 1);
      mbar_init(bars + (BAR_XSTAT + w) * 8, 1); mbar_init(bars + (BAR_ZSTAT + w) * 8, 1);
    }
    mbar_init(bars + BAR_KV * 8, 2); mbar_init(bars + BAR_PRO * 8, 8); mbar_init(bars + BAR_TR * 8, 1); mbar_init(bars + BAR_TR2 * 8, 8); mbar_init(bars + BAR_IN * 8, 8); mbar_init(bars + BAR_XS * 8, 8); mbar_init(bars + BAR_KVL * 8, 1); mbar_init(bars + (BAR_KVL + 1) * 8, 1); mbar_init(bars + BAR_GO * 8, 1); mbar_init(bars + BAR_PUBA * 8, 2); mbar_init(bars + BAR_PUBB * 8, 2);
    asm volatile("fence.mbarrier_init.release.cluster;" ::: "memory");
  }
  __syncthreads();

  if (warp >= 8) {
    asm volatile("setmaxnreg.dec.sync.aligned.u32 104;");
    unsigned ep1;
    asm volatile("ld.relaxed.gpu.global.u32 %0, [%1];" : "=r"(ep1) : "l"(&g_epoch) : "memory");
    if (warp == 8) {
      int s = 0, pf = 0; uint32_t ph = 1, pub = 0;
      mbar_wait(bars + BAR_IN * 8, 0, ab);
#pragma unroll 1
      for (int seg = 0; seg < 10; seg++) {
        const int l = seg >= 5, sg = seg - 5 * l;
        const CUtensorMap* map = sg == 0 ? (l == 0 ? &M.x0 : &M.act) : sg == 3 ? &M.wsp : sg == 4 ? &M.h : &M.act;
        const int row = 128 * r + (sg == 0 ? l * 2 * S_ : sg == 2 ? (l == 0 ? 1 : 3) * S_ : 0);
        const int nk = sg == 3 ? 32 : sg == 4 ? 12 : 10, reps = sg == 0 ? 3 : sg == 2 ? 2 : 1;
        const int dep = sg == 0 ? (l == 0 ? -1 : C_X2) : sg == 1 ? C_O + l * 32 : sg == 2 ? C_X1 + l * 32 : sg == 4 ? C_H + l * 32 : -1;
        if (dep >= 0) {
          mbar_wait(bars + BAR_PUBA * 8, pub, ab); pub ^= 1;
          if (lane < 2) cnt_wait(dep + 2 * r + lane, (ep1 + 1) * 8, ab);
          __syncwarp();
          fence_async_global();
          PROFW(64 + (seg == 5 ? 48 : seg == 6 ? 44 : seg == 7 ? 45 : seg == 9 ? 47 : 62));
        }
#pragma unroll 1
        for (int i = 0, kb = 0; i < nk * reps; i++) {
          mbar_wait(emptyA + s * 8, ph, ab);
          if (elect_one()) {
            mbar_expect_tx(fullA + s * 8, A_SLOT); tma_load(sb + OFF_A + s * A_SLOT, map, kb * 64, row, fullA + s * 8);
            if (pf < 32 && (seg > 0 || i >= 5)) asm volatile("cp.async.bulk.prefetch.L2.global [%0], %1;" :: "l"(P.wsp + (size_t)(128 * r + 16 * j) * S_ + pf * 1024), "r"(2048) : "memory");
          }
          __syncwarp();
          pf += (seg > 0 || i >= 5);
          if (++kb == nk) kb = 0;
          if (++s == SA) { s = 0; ph ^= 1; }
        }
      }
    } else if (warp == 9) {
      int s = 0; uint32_t ph = 1;
      mbar_wait(bars + BAR_GO * 8, 0, ab);
#pragma unroll 1
      for (int seg = 0; seg < 16; seg++) {
        const int l = seg >> 3, sg = seg & 7;
        const CUtensorMap* map = sg < 3 ? &M.wq : sg == 3 ? &M.wo : sg < 6 ? &M.wi : sg == 6 ? &M.z : &M.wout;
        const int row = sg < 3 ? 240 * j + 80 * sg : sg == 3 || sg == 7 ? 80 * j : sg < 6 ? 192 * j + 96 * (sg - 4) : 96 * j;
        const int nk = sg == 6 ? 32 : sg == 7 ? 12 : 10;
        const uint32_t bytes = sg >= 4 && sg <= 6 ? 12288 : 10240;
        int dep = -1; unsigned n = 0;
        if (sg == 6) { dep = C_Z2 + l * 8 + j; n = 32; }
        else if (l == 0) {
          if (sg == 3) { dep = C_BGA; n = 680; } else if (sg == 7) { dep = C_BGB; n = 240; }
        }
        if (dep >= 0) {
          if (sg == 6) mbar_wait(bars + BAR_PUBB * 8, l, ab);
          cnt_wait_warp(dep, (ep1 + 1) * n, ab);
          fence_async_global(); PROFW(64 + (seg == 0 ? 55 : seg == 3 ? 57 : seg == 14 ? 46 : 62));
        }
        if (seg < 3) {
          if (lane < 10) cnt_wait(C_W + 10 * (4 * (seg == 0 ? 1 : seg == 1 ? 2 : 0) + (j >> 1)) + lane, ep1 + 1, ab);
          __syncwarp();
          fence_async_global();
          if (seg == 0) PROFW(64 + 55);
        }
#pragma unroll 1
        for (int kb = 0; kb < nk; kb++) {
          mbar_wait(emptyB + s * 8, ph, ab);
          if (elect_one()) { mbar_expect_tx(fullB + s * 8, bytes); tma_load(sb + OFF_B + s * B_SLOT, map, kb * 64, row, fullB + s * 8); }
          __syncwarp();
          if (++s == SB) { s = 0; ph ^= 1; }
        }
      }
    } else {
      const int hw = warp - 10;
      const uint32_t stg = sb + OFF_STG + hw * STG_WG, statS = sb + OFF_STAT + hw * 512;
      const uint32_t ready = bars + (BAR_STREADY + hw) * 8, freeb = bars + (BAR_STFREE + hw) * 8;
      const int rowt = 128 * r + 64 * hw;
      if (hw == 0 && lane < (int)(sizeof(Maps) / sizeof(CUtensorMap)))
        asm volatile("prefetch.tensormap [%0];" :: "l"(reinterpret_cast<const CUtensorMap*>(&M) + lane) : "memory");
      if (hw == 1) {
        const int u = b + 128 * lane;
        if (lane == 0) mbar_expect_tx(bars + BAR_TR * 8, ((920 - b + 127) >> 7) * 4096);
        if (lane < 4) sts128(sb + OFF_STAT + 896 + lane * 16, 0u, 0u, 0u, 0u);
        fence_async_smem();
        mbar_wait(bars + BAR_IN * 8, 0, ab);
        if (lane < 8 && u < 920) {
          const TrUnit t = tr_unit(u);
          tma_load(sb + TR_IN + lane * 4096, t.which == 0 ? &M.lWo : t.which == 1 ? &M.lWi : &M.lWout, t.n0, t.k0, bars + BAR_TR * 8);
        }
      }
      if (hw == 0) {
        mbar_wait(bars + BAR_PRO * 8, 0, ab);
        PROFW(64 + 35);
        if (elect_one()) {
          if (b < 120) {
            const int kr = b % 10, cg = b / 10, t = cg >> 2, part = t == 1 ? 0 : (t == 2 ? 1 : 2);
#pragma unroll
            for (int gi = 0; gi < 2; gi++) {
              const int n = 240 * (2 * (cg & 3) + gi) + 80 * part;
              tma_store2(&M.wq, sb + PRO_W + gi * 10240, 64 * kr, n);
              bulk_reduce_add_f32(g_csq + (ep1 & 1) * 1920 + n, sb + PRO_CS + gi * 320, 320);
            }
          }
          bulk_store(g_kv + ((ep1 & 1) ^ 1) * 61440 + b * 480, sb + PRO_ZERO, 1920);
          if (b < 120) bulk_store(g_csq + ((ep1 & 1) ^ 1) * 1920 + 16 * b, sb + PRO_ZERO, 64);
          bulk_commit_wait();
          mbar_arrive(bars + BAR_GO * 8);
          if (b < 120) {
            asm volatile("fence.proxy.async.global;" ::: "memory");
            asm volatile("st.release.gpu.global.u32 [%0], %1;" :: "l"(&g_cnt[(C_W + b) * 32]), "r"(ep1 + 1) : "memory");
          }
        }
        __syncwarp();
        PROFW(64 + 53);
        mbar_wait(bars + BAR_XS * 8, 0, ab);
        if (elect_one()) { bulk_store(g_xstat + r * 1024 + j * 128, sb + OFF_XRS, 1024); bulk_commit_wait(); cnt_add(C_X0 + r, 7); }
        __syncwarp();
      }
      uint32_t rph = 0;
#pragma unroll 1
      for (int it = 0; it < 15; it++) {
        const int l = it >= 8, jb = it == 0 ? 6 : it - 1 - 7 * l;
        const int lr = l * 32 + 2 * r + hw;
        const int xb = it == 0 ? 0 : jb == 2 ? (l == 0 ? 1 : 3) : 2;
        int cnt = -1;
        if (jb == 0) cnt = C_KV + l * 8 + j; else if (jb == 1) cnt = C_O + lr; else if (jb == 2) cnt = C_X1 + lr;
        else if (jb == 4) cnt = C_Z2 + l * 8 + j; else if (jb == 5) cnt = C_H + lr; else if (l == 0) cnt = C_X2 + 2 * r + hw;
        float2* xst = g_xstat + (xb * 16 + r) * 1024 + 64 * hw;
        if (it > 0 && jb != 3) {
          mbar_wait(ready, rph, ab); rph ^= 1;
          if (it == 8 && hw == 0) PROFW(64 + 36);
          if (it >= 7 && hw == 0) PROFW(64 + 3 * (it - 7));
          if (elect_one()) {
            if (jb == 0) bulk_reduce_add_f32(g_kv + (ep1 & 1) * 61440 + (l * 8 + j) * 3840 + hw * 1920, stg + KVS_OFF, 7680);
            else if (jb == 4) tma_store2(&M.sZ, stg, rowt, 96 * j);
            else if (jb == 5) tma_store3(&M.sH, stg, 0, rowt, 3 * j);
            else if (jb == 6 && l == 1) tma_store2(&M.sOut, stg, 80 * j, rowt);
            else {
              tma_store2(&M.sAct, stg, 80 * j, (jb == 1 ? 0 : xb * S_) + rowt);
              if (jb != 1) bulk_store(xst + j * 128, statS, 512);
            }
            asm volatile("cp.async.bulk.commit_group;" ::: "memory");
            asm volatile("cp.async.bulk.wait_group.read 0;" ::: "memory");
            if (jb != 1 && jb != 5) mbar_arrive(freeb);
            if (it >= 7 && hw == 0) PROF_ST_IF(64 + 3 * (it - 7) + 1);
            asm volatile("cp.async.bulk.wait_group 0;" ::: "memory");
            if (cnt >= 0) {
              cnt_add(cnt, jb);
              if (it >= 7 && hw == 0) PROF_ST_IF(64 + 3 * (it - 7) + 2);
              if (jb != 0) mbar_arrive(bars + (jb == 4 ? BAR_PUBB : BAR_PUBA) * 8);
            }
            if (jb == 1 || jb == 5) {
              const int hl = 2 * l + (jb == 5);
              mbar_expect_tx(freeb, 10240);
              tma_load(stg, hl == 0 ? &M.rX0 : &M.sAct, 80 * j, hl * S_ + rowt, freeb);
            }
          }
          __syncwarp();
        }
        if (jb == 0) {
          if (it == 8 && hw == 0) PROFW(64 + 37);
          cnt_wait_warp(cnt, (ep1 + 1) * 32, ab);
          if (it == 8 && hw == 0) PROFW(64 + 38);
          fence_async_global();
          if (elect_one()) {
            mbar_expect_tx(bars + (BAR_KVL + hw) * 8, 7680);
            asm volatile("cp.async.bulk.shared::cluster.global.mbarrier::complete_tx::bytes [%0], [%1], %2, [%3];"
                         :: "r"(stg + KVS_OFF), "l"(g_kv + (ep1 & 1) * 61440 + (l * 8 + j) * 3840 + hw * 1920), "r"(7680), "r"(bars + (BAR_KVL + hw) * 8) : "memory");
          }
          __syncwarp();
          mbar_wait(bars + (BAR_KVL + hw) * 8, l, ab);
          float4 a[2][10];
#pragma unroll
          for (int u = 0; u < 2; u++)
#pragma unroll
            for (int c = 0; c < 10; c++) {
              a[u][c] = make_float4(0.f, 0.f, 0.f, 0.f);
              if (u == 0 || lane < 16)
                asm volatile("ld.shared.v4.f32 {%0, %1, %2, %3}, [%4];" : "=f"(a[u][c].x), "=f"(a[u][c].y), "=f"(a[u][c].z), "=f"(a[u][c].w)
                             : "r"(stg + KVS_OFF + (lane + 32 * u) * 160 + c * 16));
            }
          __syncwarp();
#pragma unroll
          for (int u = 0; u < 2; u++) {
            if (u == 0 || lane < 16) {
              const int hn = lane + 32 * u, h = hn >= 24, n = hn - 24 * h;
              const uint32_t dst = stg + KVS_OFF + h * 2304 + (n >> 3) * 768 + (n & 7) * 16;
#pragma unroll
              for (int kc = 0; kc < 5; kc++)
                sts128(dst + kc * 128, pack2(a[u][2 * kc].x, a[u][2 * kc].y), pack2(a[u][2 * kc].z, a[u][2 * kc].w),
                       pack2(a[u][2 * kc + 1].x, a[u][2 * kc + 1].y), pack2(a[u][2 * kc + 1].z, a[u][2 * kc + 1].w));
              sts128(dst + 5 * 128, 0u, 0u, 0u, 0u);
            }
          }
          fence_async_smem();
          __syncwarp();
          if (lane == 0) mbar_arrive(bars + BAR_KV * 8);
          if (it == 8 && hw == 0) PROFW(64 + 39);
        } else if (jb == 3) {
          const uint4* part = g_zstat + r * 1024 + 64 * hw + lane;
          const uint32_t tag = 2 * ep1 + 1 + l;
          float sum[2] = {0.f, 0.f}, sq[2] = {0.f, 0.f};
#pragma unroll 1
          for (uint32_t n = 0;; n++) {
            uint64_t v[2][8][2];
#pragma unroll
            for (int h = 0; h < 2; h++)
#pragma unroll
              for (int c = 0; c < 8; c++)
                asm volatile("ld.relaxed.gpu.global.v2.b64 {%0, %1}, [%2];" : "=l"(v[h][c][0]), "=l"(v[h][c][1]) : "l"(part + c * 128 + 32 * h) : "memory");
            bool ok = true;
#pragma unroll
            for (int h = 0; h < 2; h++) {
              sum[h] = 0.f; sq[h] = 0.f;
#pragma unroll
              for (int c = 0; c < 8; c++) {
                ok = ok && (uint32_t)(v[h][c][0] >> 32) == tag && (uint32_t)(v[h][c][1] >> 32) == tag;
                sum[h] += __uint_as_float((uint32_t)v[h][c][0]); sq[h] += __uint_as_float((uint32_t)v[h][c][1]);
              }
            }
            if (__all_sync(0xffffffffu, ok)) break;
            if (lds32v(ab) != 0) break;
            if (n > (1u << 18)) { asm volatile("st.volatile.shared.u32 [%0], 1;" :: "r"(ab) : "memory"); break; }
          }
#pragma unroll
          for (int h = 0; h < 2; h++) {
            const float m = sum[h] * (1.f / 768.f);
            sts64f(sb + OFF_ZRS + hw * 512 + (lane + 32 * h) * 8, m, rsqrtf(fmaxf(sq[h] * (1.f / 768.f) - m * m, 0.f) + 1e-5f));
          }
          __syncwarp();
          if (lane == 0) mbar_arrive(bars + (BAR_ZSTAT + hw) * 8);
        } else if (jb == 2 || (jb == 6 && l == 0)) {
          if (it == 0) {
            if (lane < 30) cnt_wait(C_W + 10 * (4 * (lane / 10) + (j >> 1)) + lane % 10, ep1 + 1, ab);
            __syncwarp();
            cnt_wait_warp(C_X0 + r, (ep1 + 1) * 8, ab);
#pragma unroll
            for (int c = 0; c < 8; c++)
              if (lane + 32 * c < 240) sts32(sb + OFF_CSQ + (lane + 32 * c) * 4, __float_as_uint(__ldcg(&g_csq[(ep1 & 1) * 1920 + 240 * j + lane + 32 * c])));
          } else cnt_wait_warp(cnt, (ep1 + 1) * 8, ab);
          if (it == 3) {
            cnt_wait_warp(C_BGA, (ep1 + 1) * 680, ab);
#pragma unroll
            for (int c = 0; c < 6; c++) sts32(sb + OFF_CSI + (lane + 32 * c) * 4, __float_as_uint(__ldcg(&g_csi[(ep1 & 1) * 1536 + 192 * j + lane + 32 * c])));
          }
          const float2* part = xst;
          const float inv_n = 1.f / 640.f;
          const uint32_t dst = sb + OFF_XRS + hw * 512;
          float2 v[2][8];
#pragma unroll
          for (int h = 0; h < 2; h++)
#pragma unroll
            for (int c = 0; c < 8; c++) v[h][c] = __ldcg(part + c * 128 + lane + 32 * h);
#pragma unroll
          for (int h = 0; h < 2; h++) {
            float s = 0.f, t = 0.f;
#pragma unroll
            for (int c = 0; c < 8; c++) { s += v[h][c].x; t += v[h][c].y; }
            const float m = s * inv_n;
            sts64f(dst + (lane + 32 * h) * 8, m, rsqrtf(fmaxf(t * inv_n - m * m, 0.f) + 1e-5f));
          }
          __syncwarp();
          if (lane == 0) mbar_arrive(bars + (BAR_XSTAT + hw) * 8);
          if (it == 0 && hw == 1) {
            const int nu = (920 - b + 127) >> 7;
            const TrUnit t = tr_unit(min(b + 128 * (lane & 7), 919));
            mbar_wait(bars + BAR_TR2 * 8, 0, ab);
#pragma unroll 1
            for (int i = 0; i < nu; i++) {
              const int which = __shfl_sync(0xffffffffu, t.which, i), k0 = __shfl_sync(0xffffffffu, t.k0, i), drow = __shfl_sync(0xffffffffu, t.drow, i);
              if (elect_one()) {
                tma_store2(which == 0 ? &M.sWo : which == 1 ? &M.sWi : &M.sWout, sb + TR_OUT + i * 4096, k0, drow);
                if (which == 1) bulk_reduce_add_f32(g_csi + (ep1 & 1) * 1536 + drow, sb + OFF_ZRS + i * 128, 128);
                if (i == 0 && b < 96) bulk_store(g_csi + ((ep1 & 1) ^ 1) * 1536 + 16 * b, sb + OFF_STAT + 896, 64);
                asm volatile("cp.async.bulk.commit_group;" ::: "memory");
                asm volatile("cp.async.bulk.wait_group.read 0;" ::: "memory");
              }
              __syncwarp();
            }
            if (elect_one()) {
              mbar_arrive(bars + BAR_STFREE * 8); mbar_arrive(bars + (BAR_STFREE + 1) * 8);
              asm volatile("cp.async.bulk.wait_group 0;" ::: "memory");
              const int na = (680 - b + 127) >> 7;
              cnt_add(C_BGA, 7, na);
              if (nu > na) cnt_add(C_BGB, 7, nu - na);
            }
            __syncwarp();
            PROFW(64 + 58);
          }
        }
      }
      if (b == 0 && hw == 0 && lane == 0) *(volatile unsigned*)&g_epoch = ep1 + 1;
      PROFW(64 + (hw == 0 ? 49 : 59));
    }
  } else {
    asm volatile("setmaxnreg.inc.sync.aligned.u32 200;");
    const int wg = warp >> 2, w4 = warp & 3;
    Pipe p;
    p.ab = ab; p.fullA = fullA; p.emptyA = emptyA; p.fullB = fullB; p.emptyB = emptyB;
    p.dA = make_desc(sb + OFF_A + wg * 8192, 16, 1024, 1); p.dB = make_desc(sb + OFF_B, 16, 1024, 1);
    p.sa = 0; p.sb = 0; p.pa = 0; p.pb = 0; p.leader = (threadIdx.x & 127) == 0;
    Stage st;
    st.ready = bars + (BAR_STREADY + wg) * 8; st.freeb = bars + (BAR_STFREE + wg) * 8; st.ab = ab; st.ph = 0;
    const uint32_t sb_ = sb;
    const int lane_ = lane;
    unsigned ztag;
    asm volatile("ld.relaxed.gpu.global.u32 %0, [%1];" : "=r"(ztag) : "l"(&g_epoch) : "memory");
    ztag = 2 * ztag + 1;
    PROF(64 + 51);
    prologue(P, b, r, j, sb, warp, lane);
    PROF(1);

#pragma unroll 1
    for (int hl = 0; hl < 4; hl++) {
      const int l = hl >> 1;
      const uint32_t sb = uniform(sb_);
      const int lane = opaque(lane_), g = lane >> 2, q = lane & 3;
      const int rw = 16 * w4 + g;
      const int row0 = 128 * r + 64 * wg + rw;
      const uint32_t stg = sb + OFF_STG + wg * STG_WG;
      const uint32_t statS = sb + OFF_STAT + wg * 512;
      const uint32_t bars = sb + OFF_BAR;
      if ((hl & 1) == 0) {
        float m0, r0, m1, r1;
        {
          float ak[40], av[40], kv0[12], kv1[12];
          gemm1<80>(ak, p, 10);
          PROF(2 + l * 24);
          gemm1<80>(av, p, 10);
          PROF(3 + l * 24);
          mbar_wait(bars + (BAR_XSTAT + wg) * 8, 0, p.ab);
          const float2 sa = lds64f(sb + OFF_XRS + (64 * wg + rw) * 8), sc = lds64f(sb + OFF_XRS + (64 * wg + rw + 8) * 8);
          m0 = sa.x; r0 = sa.y; m1 = sc.x; r1 = sc.y;
          st.acquire();
          {
            const uint32_t pv = stg + VS_OFF + q * VS_HS + rw * 16;
            uint32_t v0[10], v1[10];
#pragma unroll
            for (int i = 0; i < 10; i++) {
              const float2 cv = lds64f(sb + OFF_CSQ + (80 + 8 * i + 2 * q) * 4);
              v0[i] = pack2(r0 * fmaf(-m0, cv.x, av[4 * i]), r0 * fmaf(-m0, cv.y, av[4 * i + 1]));
              v1[i] = pack2(r1 * fmaf(-m1, cv.x, av[4 * i + 2]), r1 * fmaf(-m1, cv.y, av[4 * i + 3]));
            }
            sts128(pv, v0[0], v0[1], v0[2], v0[3]); sts128(pv + 1024, v0[4], v0[5], v0[6], v0[7]); sts128(pv + 2048, v0[8], v0[9], 0x00003f80u, 0u);
            sts128(pv + 128, v1[0], v1[1], v1[2], v1[3]); sts128(pv + 128 + 1024, v1[4], v1[5], v1[6], v1[7]); sts128(pv + 128 + 2048, v1[8], v1[9], 0x00003f80u, 0u);
          }
          feature_rows(ak, sb + OFF_CSQ + q * 8, m0, r0, m1, r1, stg + q * PHK_HS + rw * 16, false);
          fresh(kv0); fresh(kv1);
          fence_async_smem();
          bar_sync(3, 256);
          PROF(19 + l * 24);
          const uint32_t s0 = sb + OFF_STG + 2 * wg * PHK_HS, s1 = sb + OFF_STG + VS_OFF + 2 * wg * VS_HS;
          wg_fence();
#pragma unroll
          for (int s = 0; s < 8; s++) {
            const uint32_t o = (s >> 2) * STG_WG + (s & 3) * 256;
            wgmma<24, 1, 1>(kv0, make_desc(s0 + o, 128, 1024, 0), make_desc(s1 + o, 128, 1024, 0), s > 0);
            wgmma<24, 1, 1>(kv1, make_desc(s0 + PHK_HS + o, 128, 1024, 0), make_desc(s1 + VS_HS + o, 128, 1024, 0), s > 0);
          }
          wg_commit();
          wg_wait<0>();
          pin(kv0); pin(kv1);
          bar_sync(3, 256);
          const uint32_t ks = stg + KVS_OFF + (2 * q * 40 + rw) * 4;
#pragma unroll
          for (int i = 0; i < 3; i++) {
#pragma unroll
            for (int e = 0; e < 2; e++) {
              const uint32_t a = ks + (8 * i + e) * 160;
              if (rw < 40) { sts32(a, __float_as_uint(kv0[4 * i + e])); sts32(a + 3840, __float_as_uint(kv1[4 * i + e])); }
              if (rw + 8 < 40) { sts32(a + 32, __float_as_uint(kv0[4 * i + 2 + e])); sts32(a + 3840 + 32, __float_as_uint(kv1[4 * i + 2 + e])); }
            }
          }
          st.publish();
        }
        PROF(20 + l * 24);
        {
          float aq[40];
          gemm1<80>(aq, p, 10);
          PROF(4 + l * 24);
          feature_rows(aq, sb + OFF_CSQ + 160 * 4 + q * 8, m0, r0, m1, r1, stg + q * PHQ_HS + rw * 16, true);
          fence_async_smem();
        }
        PROF(5 + l * 24);
        float o0[12], o1[12], o2[12], o3[12];
        fresh(o0); fresh(o1); fresh(o2); fresh(o3);
        bar_sync(1 + wg, 128);
        mbar_wait(bars + BAR_KV * 8, l, p.ab);
        PROF(6 + l * 24);
        wg_fence();
#pragma unroll
        for (int s = 0; s < 3; s++) {
          const uint32_t kb0 = sb + OFF_STG + KVS_OFF + s * 256, kb1 = kb0 + STG_WG;
          wgmma<24, 0, 0>(o0, make_desc(stg + 0 * PHQ_HS + s * 2048, 1024, 128, 0), make_desc(kb0, 128, 768, 0), s > 0);
          wgmma<24, 0, 0>(o1, make_desc(stg + 1 * PHQ_HS + s * 2048, 1024, 128, 0), make_desc(kb0 + 2304, 128, 768, 0), s > 0);
          wgmma<24, 0, 0>(o2, make_desc(stg + 2 * PHQ_HS + s * 2048, 1024, 128, 0), make_desc(kb1, 128, 768, 0), s > 0);
          wgmma<24, 0, 0>(o3, make_desc(stg + 3 * PHQ_HS + s * 2048, 1024, 128, 0), make_desc(kb1 + 2304, 128, 768, 0), s > 0);
        }
        wg_commit();
        wg_wait<0>();
        pin(o0); pin(o1); pin(o2); pin(o3);
        bar_sync(1 + wg, 128);
        st.acquire();
        auto emit = [&](const float (&o)[12], int h) {
          const float d0 = rcp(__shfl_sync(0xffffffffu, o[8], (lane & ~3) | 2) + 1e-6f);
          const float d1 = rcp(__shfl_sync(0xffffffffu, o[10], (lane & ~3) | 2) + 1e-6f);
          const uint32_t a0 = stg + rw * 160 + (20 * h + 2 * q) * 2, a1 = a0 + 8 * 160;
          sts32(a0, pack2(o[0] * d0, o[1] * d0)); sts32(a1, pack2(o[2] * d1, o[3] * d1));
          sts32(a0 + 16, pack2(o[4] * d0, o[5] * d0)); sts32(a1 + 16, pack2(o[6] * d1, o[7] * d1));
          if (q < 2) { sts32(a0 + 32, pack2(o[8] * d0, o[9] * d0)); sts32(a1 + 32, pack2(o[10] * d1, o[11] * d1)); }
        };
        emit(o0, 0); emit(o1, 1); emit(o2, 2); emit(o3, 3);
        st.publish();
        PROF(7 + l * 24);
      } else {
        float m0, r0, m1, r1;
        uint32_t z2a[12], z2b[12];
        {
          float a2[48];
          gemm1<96>(a2, p, 10);
          PROF(10 + l * 24);
          mbar_wait(bars + (BAR_XSTAT + wg) * 8, 1, p.ab);
          const float2 sa = lds64f(sb + OFF_XRS + (64 * wg + rw) * 8), sc = lds64f(sb + OFF_XRS + (64 * wg + rw + 8) * 8);
          m0 = sa.x; r0 = sa.y; m1 = sc.x; r1 = sc.y;
          gelu_rows<true>(a2, sb + OFF_CSI + q * 8, m0, r0, m1, r1, z2a, z2b, g_zstat + (r * 8 + j) * 128 + 64 * wg + rw, ztag + l, q == 0);
        }
        PROF(21 + l * 24);
        float a1[48];
        gemm1<96>(a1, p, 5);
        PROF(11 + l * 24);
        mbar_wait(bars + (BAR_ZSTAT + wg) * 8, l, p.ab);
        PROF(12 + l * 24);
        {
          const float2 a = lds64f(sb + OFF_ZRS + (64 * wg + rw) * 8), c = lds64f(sb + OFF_ZRS + (64 * wg + rw + 8) * 8);
          const float an = -a.x * a.y, cn = -c.x * c.y;
          st.acquire();
          const int mi = lane >> 3, fr = lane & 7;
          const uint32_t za = stg + (8 * (mi >> 1) + fr) * 128 + (((2 * w4 + (mi & 1)) ^ fr) << 4);
#pragma unroll
          for (int i = 0; i < 12; i += 2)
            stsm4t(za + i * 1024,
                   pack2(fmaf(bf_lo(z2a[i]), a.y, an), fmaf(bf_hi(z2a[i]), a.y, an)), pack2(fmaf(bf_lo(z2b[i]), c.y, cn), fmaf(bf_hi(z2b[i]), c.y, cn)),
                   pack2(fmaf(bf_lo(z2a[i + 1]), a.y, an), fmaf(bf_hi(z2a[i + 1]), a.y, an)), pack2(fmaf(bf_lo(z2b[i + 1]), c.y, cn), fmaf(bf_hi(z2b[i + 1]), c.y, cn)));
          st.publish();
        }
        PROF(13 + l * 24);
        gemm1<96, true>(a1, p, 5);
        PROF(22 + l * 24);
        uint32_t z1a[12], z1b[12];
        gelu_rows<false>(a1, sb + OFF_CSI + 96 * 4 + q * 8, m0, r0, m1, r1, z1a, z1b, nullptr, 0u, false);
        PROF(14 + l * 24);
        const float bs0 = __bfloat162float(P.bsp[row0]), bs1 = __bfloat162float(P.bsp[row0 + 8]);
        float acc[48];
        gemm1<96>(acc, p, 32);
        PROF(15 + l * 24);
        st.acquire();
        const int rr = 16 * w4 + (lane & 15), hi = lane >> 4, sw = (rr >> 1) & 3;
#pragma unroll
        for (int i = 0; i < 12; i += 2)
          stsm4(stg + (i >> 2) * 4096 + rr * 64 + ((((i & 3) + hi) ^ sw) << 4),
                pack2(bf_lo(z1a[i]) * (acc[4 * i] + bs0), bf_hi(z1a[i]) * (acc[4 * i + 1] + bs0)),
                pack2(bf_lo(z1b[i]) * (acc[4 * i + 2] + bs1), bf_hi(z1b[i]) * (acc[4 * i + 3] + bs1)),
                pack2(bf_lo(z1a[i + 1]) * (acc[4 * i + 4] + bs0), bf_hi(z1a[i + 1]) * (acc[4 * i + 5] + bs0)),
                pack2(bf_lo(z1b[i + 1]) * (acc[4 * i + 6] + bs1), bf_hi(z1b[i + 1]) * (acc[4 * i + 7] + bs1)));
        st.publish();
        PROF(16 + l * 24);
      }
      {
        float acc[40];
        gemm1<80>(acc, p, (hl & 1) ? 12 : 10);
        PROF(((hl & 1) ? 17 : 8) + l * 24);
        st.acquire();
        const uint32_t rowaddr = stg + (16 * w4 + (lane & 15)) * 160 + (lane >> 4) * 16;
        float s0 = 0.f, t0 = 0.f, s1 = 0.f, t1 = 0.f;
#pragma unroll
        for (int i = 0; i < 10; i += 2) {
          uint32_t x0, x1, x2, x3;
          asm volatile("ldmatrix.sync.aligned.m8n8.x4.shared.b16 {%0, %1, %2, %3}, [%4];" : "=r"(x0), "=r"(x1), "=r"(x2), "=r"(x3) : "r"(rowaddr + i * 16));
          x0 = pack2(acc[4 * i] + bf_lo(x0), acc[4 * i + 1] + bf_hi(x0));
          x1 = pack2(acc[4 * i + 2] + bf_lo(x1), acc[4 * i + 3] + bf_hi(x1));
          x2 = pack2(acc[4 * i + 4] + bf_lo(x2), acc[4 * i + 5] + bf_hi(x2));
          x3 = pack2(acc[4 * i + 6] + bf_lo(x3), acc[4 * i + 7] + bf_hi(x3));
          stsm4(rowaddr + i * 16, x0, x1, x2, x3);
          s0 += (bf_lo(x0) + bf_hi(x0)) + (bf_lo(x2) + bf_hi(x2)); s1 += (bf_lo(x1) + bf_hi(x1)) + (bf_lo(x3) + bf_hi(x3));
          t0 = fmaf(bf_lo(x0), bf_lo(x0), fmaf(bf_hi(x0), bf_hi(x0), fmaf(bf_lo(x2), bf_lo(x2), fmaf(bf_hi(x2), bf_hi(x2), t0))));
          t1 = fmaf(bf_lo(x1), bf_lo(x1), fmaf(bf_hi(x1), bf_hi(x1), fmaf(bf_lo(x3), bf_lo(x3), fmaf(bf_hi(x3), bf_hi(x3), t1))));
        }
#pragma unroll
        for (int m = 1; m <= 2; m <<= 1) {
          s0 += __shfl_xor_sync(0xffffffffu, s0, m); t0 += __shfl_xor_sync(0xffffffffu, t0, m);
          s1 += __shfl_xor_sync(0xffffffffu, s1, m); t1 += __shfl_xor_sync(0xffffffffu, t1, m);
        }
        if (q == 0) { sts64f(statS + rw * 8, s0, t0); sts64f(statS + (rw + 8) * 8, s1, t1); }
        st.publish();
        PROF(((hl & 1) ? 18 : 9) + l * 24);
      }
    }
    PROFG(64 + 61);
  }
}

typedef CUresult (*EncodeFn)(CUtensorMap*, CUtensorMapDataType, cuuint32_t, void*, const cuuint64_t*, const cuuint64_t*, const cuuint32_t*,
                             const cuuint32_t*, CUtensorMapInterleave, CUtensorMapSwizzle, CUtensorMapL2promotion, CUtensorMapFloatOOBfill);

CUtensorMap map2d(EncodeFn fn, const void* ptr, uint64_t rows, uint64_t cols, uint32_t box_rows, uint32_t box_cols, CUtensorMapSwizzle sw) {
  CUtensorMap m;
  cuuint64_t dims[2] = {cols, rows}, strides[1] = {cols * 2};
  cuuint32_t box[2] = {box_cols, box_rows}, es[2] = {1, 1};
  fn(&m, CU_TENSOR_MAP_DATA_TYPE_BFLOAT16, 2, const_cast<void*>(ptr), dims, strides, box, es, CU_TENSOR_MAP_INTERLEAVE_NONE, sw,
     CU_TENSOR_MAP_L2_PROMOTION_L2_256B, CU_TENSOR_MAP_FLOAT_OOB_FILL_NONE);
  return m;
}

}

extern "C" void kernel_launch(void* const* d_in, const int* in_sizes, int n_in, void* d_out, int out_size) {
  (void)in_sizes; (void)n_in; (void)out_size;
  static bool init = false;
  static Maps M;
  static Params P;
  static void* cached_ptrs[10];
  bool same = init;
  for (int i = 0; i < 9 && same; i++) same = cached_ptrs[i] == d_in[i];
  same = same && cached_ptrs[9] == d_out;
  if (!same) {
    void* fp = nullptr;
    cudaDriverEntryPointQueryResult st;
    cudaGetDriverEntryPoint("cuTensorMapEncodeTiled", &fp, cudaEnableDefault, &st);
    EncodeFn fn = (EncodeFn)fp;
    void *act, *h, *z, *wq, *wo, *wi, *wout;
    cudaGetSymbolAddress(&act, g_act); cudaGetSymbolAddress(&h, g_h); cudaGetSymbolAddress(&z, g_z);
    cudaGetSymbolAddress(&wq, g_Wq); cudaGetSymbolAddress(&wo, g_Wo); cudaGetSymbolAddress(&wi, g_Wi); cudaGetSymbolAddress(&wout, g_Wout);
    const CUtensorMapSwizzle S128 = CU_TENSOR_MAP_SWIZZLE_128B;
    M.x0 = map2d(fn, d_in[0], 2048, 640, 128, 64, S128);
    M.act = map2d(fn, act, 4 * 2048, 640, 128, 64, S128);
    M.wsp = map2d(fn, d_in[6], 2048, 2048, 128, 64, S128);
    M.h = map2d(fn, h, 2048, 768, 128, 64, S128);
    M.wq = map2d(fn, wq, 1920, 640, 80, 64, S128);
    M.wo = map2d(fn, wo, 640, 640, 80, 64, S128);
    M.wi = map2d(fn, wi, 1536, 640, 96, 64, S128);
    M.z = map2d(fn, z, 768, 2048, 96, 64, S128);
    M.wout = map2d(fn, wout, 640, 768, 80, 64, S128);
    M.sAct = map2d(fn, act, 4 * 2048, 640, 64, 80, CU_TENSOR_MAP_SWIZZLE_NONE);
    M.sOut = map2d(fn, d_out, 2048, 640, 64, 80, CU_TENSOR_MAP_SWIZZLE_NONE);
    M.sZ = map2d(fn, z, 768, 2048, 96, 64, S128);
    M.lWo = map2d(fn, d_in[3], 640, 640, 64, 32, CU_TENSOR_MAP_SWIZZLE_64B);
    M.lWi = map2d(fn, d_in[5], 640, 1536, 64, 32, CU_TENSOR_MAP_SWIZZLE_64B);
    M.lWout = map2d(fn, d_in[8], 768, 640, 64, 32, CU_TENSOR_MAP_SWIZZLE_64B);
    M.sWo = map2d(fn, wo, 640, 640, 32, 64, S128);
    M.sWi = map2d(fn, wi, 1536, 640, 32, 64, S128);
    M.sWout = map2d(fn, wout, 640, 768, 32, 64, S128);
    M.rX0 = map2d(fn, d_in[0], 2048, 640, 64, 80, CU_TENSOR_MAP_SWIZZLE_NONE);
    {
      cuuint64_t dims[3] = {32, 2048, 24}, strides[2] = {768 * 2, 64};
      cuuint32_t box[3] = {32, 64, 3}, es[3] = {1, 1, 1};
      fn(&M.sH, CU_TENSOR_MAP_DATA_TYPE_BFLOAT16, 3, h, dims, strides, box, es, CU_TENSOR_MAP_INTERLEAVE_NONE, CU_TENSOR_MAP_SWIZZLE_64B,
         CU_TENSOR_MAP_L2_PROMOTION_NONE, CU_TENSOR_MAP_FLOAT_OOB_FILL_NONE);
    }
    P.x = (const __nv_bfloat16*)d_in[0]; P.wqkv = (const __nv_bfloat16*)d_in[1]; P.wphi = (const __nv_bfloat16*)d_in[2];
    P.wo = (const __nv_bfloat16*)d_in[3]; P.win = (const __nv_bfloat16*)d_in[5]; P.wsp = (const __nv_bfloat16*)d_in[6];
    P.bsp = (const __nv_bfloat16*)d_in[7]; P.wout = (const __nv_bfloat16*)d_in[8];
    cudaFuncSetAttribute(mega_kernel, cudaFuncAttributeMaxDynamicSharedMemorySize, SMEM_BYTES);
    for (int i = 0; i < 9; i++) cached_ptrs[i] = d_in[i];
    cached_ptrs[9] = d_out;
    init = true;
  }
  mega_kernel<<<NCTA, NTHREADS, SMEM_BYTES>>>(M, P);
}
```
